```python
import torch

def _softmax(x, axis=-1):
    return torch.softmax(x, dim=axis)
def _gelu(x):
    return torch.nn.functional.gelu(x, approximate="tanh")
def _silu(x):
    return torch.nn.functional.silu(x)
def _sigmoid(x):
    return torch.sigmoid(x)
def _layernorm(x, axis=-1, eps=1e-5):
    m = x.mean(dim=axis, keepdim=True)
    v = x.var(dim=axis, keepdim=True, unbiased=False)
    return (x - m) / torch.sqrt(v + eps)
def _scatter_add(tgt, idx, src, axis=0):
    return tgt.clone().index_add_(axis, idx, src)
def _segment_sum(src, seg, n):
    out = torch.zeros((n,) + src.shape[1:], dtype=src.dtype)
    return out.index_add_(0, seg, src)
def _pad(x, pw):
    flat = tuple(v for pair in reversed(pw) for v in pair)
    return torch.nn.functional.pad(x, flat)

kernel_name = 'gated_mix__sliding_block_cached__gqa_block_cached__decode'

def setup_inputs():

    _w = (lambda a: (lambda t: t.to(torch.bfloat16) if t.is_floating_point() else t)(torch.as_tensor(a)))
    def _A_setup():
        B, Sq, D = 1, 1, 448
        Hq, Hkv, Sk, Dh = 16, 8, 8192, 256
        assert Hq % Hkv == 0, (Hq, Hkv)
        return {
            "x": _w((lambda *s: torch.randn(*s, dtype=torch.bfloat16) * 0.05)(B, Sq, D)),
            "k_cache": _w((lambda *s: torch.randn(*s, dtype=torch.bfloat16) * 3.2)(B, Hkv, Sk, Dh)),
            "v_cache": _w((lambda *s: torch.randn(*s, dtype=torch.bfloat16) * 0.05)(B, Hkv, Sk, Dh)),
            "wq": _w((lambda *s: torch.randn(*s, dtype=torch.bfloat16) * 3.2)(D, Hq * Dh) * (D ** -0.5)),
            "wo": _w((lambda *s: torch.randn(*s, dtype=torch.bfloat16) * 0.05)(Hq * Dh, D) * ((Hq * Dh) ** -0.5)),
        }
    _A_in = _A_setup()

    def _B_setup():
        B, Sq, D = 1, 1, 448
        Hq, Hkv, Sk, Dh = 16, 8, 8192, 256
        assert Hq % Hkv == 0, (Hq, Hkv)
        return {
            "x": _w((lambda *s: torch.randn(*s, dtype=torch.bfloat16) * 0.05)(B, Sq, D)),
            "k_cache": _w((lambda *s: torch.randn(*s, dtype=torch.bfloat16) * 3.2)(B, Hkv, Sk, Dh)),
            "v_cache": _w((lambda *s: torch.randn(*s, dtype=torch.bfloat16) * 0.05)(B, Hkv, Sk, Dh)),
            "wq": _w((lambda *s: torch.randn(*s, dtype=torch.bfloat16) * 3.2)(D, Hq * Dh) * (D ** -0.5)),
            "wo": _w((lambda *s: torch.randn(*s, dtype=torch.bfloat16) * 0.05)(Hq * Dh, D) * ((Hq * Dh) ** -0.5)),
        }
    _B_in = _B_setup()

    return {
        "A_x": _A_in["x"],
        "A_k_cache": _A_in["k_cache"],
        "A_v_cache": _A_in["v_cache"],
        "A_wq": _A_in["wq"],
        "A_wo": _A_in["wo"],
        "B_x": _B_in["x"],
        "B_k_cache": _B_in["k_cache"],
        "B_v_cache": _B_in["v_cache"],
        "B_wq": _B_in["wq"],
        "B_wo": _B_in["wo"],
        "gate_w": _w((lambda *s: torch.randn(*s, dtype=torch.bfloat16) * 0.1)(448) * 16.0),
    }

def reference(A_x, A_k_cache, A_v_cache, A_wq, A_wo, B_x, B_k_cache, B_v_cache, B_wq, B_wo, gate_w):
    def _A_ref(x, k_cache, v_cache, wq, wo):
        B, Sq, D = x.shape
        Hq, Dh = 16, 256
        Hkv, Sk = k_cache.shape[1], k_cache.shape[2]
        W = min(4096, max(256, Sk // 4))
        rep = Hq // Hkv
        q = (lambda x, *d: x.permute(*d))((x @ wq).reshape(B, Sq, Hq, Dh), 0, 2, 1, 3)
        k = (lambda x, n, axis: torch.repeat_interleave(x, n, dim=axis))(k_cache[:, :, Sk - W:, :], rep, axis=1)
        v = (lambda x, n, axis: torch.repeat_interleave(x, n, dim=axis))(v_cache[:, :, Sk - W:, :], rep, axis=1)
        scores = torch.einsum("bhqd,bhkd->bhqk", q, k) * (Dh ** -0.5)
        p = _softmax(scores, axis=-1)
        o = torch.einsum("bhqk,bhkd->bhqd", p, v)
        return (lambda x, *d: x.permute(*d))(o, 0, 2, 1, 3).reshape(B, Sq, Hq * Dh) @ wo

    def _B_ref(x, k_cache, v_cache, wq, wo):
        B, Sq, D = x.shape
        Hq, Dh = 16, 256
        Hkv = k_cache.shape[1]
        rep = Hq // Hkv
        q = (lambda x, *d: x.permute(*d))((x @ wq).reshape(B, Sq, Hq, Dh), 0, 2, 1, 3)
        k = (lambda x, n, axis: torch.repeat_interleave(x, n, dim=axis))(k_cache, rep, axis=1)
        v = (lambda x, n, axis: torch.repeat_interleave(x, n, dim=axis))(v_cache, rep, axis=1)
        scores = torch.einsum("bhqd,bhkd->bhqk", q, k) * (Dh ** -0.5)
        p = _softmax(scores, axis=-1)
        o = torch.einsum("bhqk,bhkd->bhqd", p, v)
        return (lambda x, *d: x.permute(*d))(o, 0, 2, 1, 3).reshape(B, Sq, Hq * Dh) @ wo

    x = A_x
    g = _sigmoid((x * gate_w).sum(-1, keepdims=True))
    a = _A_ref(x, A_k_cache, A_v_cache, A_wq, A_wo)
    b = _B_ref(x, B_k_cache, B_v_cache, B_wq, B_wo)
    return g * a + (1 - g) * b
```

```cpp
#include <cuda_runtime.h>
#include <cuda_bf16.h>
#include <cuda.h>
#include <stdint.h>

namespace {

constexpr int D_MODEL = 448;
constexpr int SK      = 8192;
constexpr int WIN     = 2048;
constexpr int NCTA    = 64;
constexpr int CL      = 8;
constexpr int NTHR    = 288;
#define NSLOT 8
constexpr int NS      = NSLOT;
constexpr int TILE    = 16384;
constexpr int WOTILE  = 16 * 896;
constexpr int T_K = 7, T_KB = 15, T_V = 47, T_VB = 55, T_O = 87, T_END = 95;
constexpr int OSTR = 72;

constexpr int SM_RING  = 0;
constexpr int SM_Q     = SM_RING + NS * TILE;
constexpr int SM_X     = SM_Q + 2048;
constexpr int SM_GW    = SM_X + 896;
constexpr int SM_QRED  = SM_GW + 896;
constexpr int SM_S     = SM_QRED + 2048;
constexpr int SM_P     = SM_S + 10240;
constexpr int SM_OP    = SM_P + 5120;
constexpr int SM_STAT  = SM_OP + 2 * 16 * OSTR * 4;
constexpr int SM_RED   = SM_STAT + 128;
constexpr int SM_OV    = SM_RED + 256;
constexpr int SM_MISC  = SM_OV + 512;
constexpr int SM_BAR   = SM_MISC + 16;
constexpr int B_FULL = 0, B_EMPTY = NS, B_X = 2 * NS, B_Q = B_X + 1, B_STAT = B_X + 2, B_O = B_X + 3;
constexpr int NBAR     = B_O + 2;
constexpr int SM_TOTAL = SM_BAR + NBAR * 8;

struct Params {
    const char* x; const char* gw;
    const char* k[2]; const char* v[2]; const char* wo[2];
    __nv_bfloat16* out;
};

__device__ uint32_t g_part[56 * NCTA * 8];
__device__ uint32_t g_epoch;
#define TRACE(i) do {} while (0)

__device__ __forceinline__ void mbar_init(uint32_t a, uint32_t c) {
    asm volatile("mbarrier.init.shared::cta.b64 [%0], %1;" ::"r"(a), "r"(c) : "memory");
}
__device__ __forceinline__ void mbar_expect(uint32_t a, uint32_t bytes) {
    asm volatile("mbarrier.arrive.expect_tx.shared::cta.b64 _, [%0], %1;" ::"r"(a), "r"(bytes) : "memory");
}
__device__ __forceinline__ void mbar_arrive(uint32_t a, uint32_t cnt) {
    asm volatile("mbarrier.arrive.shared::cta.b64 _, [%0], %1;" ::"r"(a), "r"(cnt) : "memory");
}
__device__ __forceinline__ void mbar_wait(uint32_t a, uint32_t parity) {
    uint32_t ok;
    int it = 0;
    do {
        asm volatile("{.reg .pred p; mbarrier.try_wait.parity.shared::cta.b64 p, [%1], %2; selp.u32 %0, 1, 0, p;}"
                     : "=r"(ok) : "r"(a), "r"(parity) : "memory");
        if (++it > (1 << 22)) __trap();
    } while (!ok);
}
__device__ __forceinline__ void mbar_wait_cluster(uint32_t a, uint32_t parity) {
    uint32_t ok;
    int it = 0;
    do {
        asm volatile("{.reg .pred p; mbarrier.try_wait.parity.acquire.cluster.shared::cta.b64 p, [%1], %2; selp.u32 %0, 1, 0, p;}"
                     : "=r"(ok) : "r"(a), "r"(parity) : "memory");
        if (++it > (1 << 22)) __trap();
    } while (!ok);
}
__device__ __forceinline__ void bulk_load(uint32_t dst, const void* src, uint32_t bytes, uint32_t bar, uint64_t pol) {
    asm volatile("cp.async.bulk.shared::cluster.global.mbarrier::complete_tx::bytes.L2::cache_hint [%0], [%1], %2, [%3], %4;"
                 ::"r"(dst), "l"(src), "r"(bytes), "r"(bar), "l"(pol) : "memory");
}
__device__ __forceinline__ void tensor_load(uint32_t dst, const CUtensorMap* tm, int c0, int c1, uint32_t bar, uint64_t pol) {
    asm volatile("cp.async.bulk.tensor.2d.shared::cluster.global.mbarrier::complete_tx::bytes.L2::cache_hint [%0], [%1, {%3, %4}], [%2], %5;"
                 ::"r"(dst), "l"(tm), "r"(bar), "r"(c0), "r"(c1), "l"(pol) : "memory");
}
__device__ __forceinline__ uint32_t mapa(uint32_t a, uint32_t rank) {
    uint32_t r;
    asm("mapa.shared::cluster.u32 %0, %1, %2;" : "=r"(r) : "r"(a), "r"(rank));
    return r;
}
__device__ __forceinline__ void st_async2(uint32_t a, float x, float y, uint32_t bar) {
    asm volatile("st.async.shared::cluster.mbarrier::complete_tx::bytes.v2.f32 [%0], {%1, %2}, [%3];"
                 ::"r"(a), "f"(x), "f"(y), "r"(bar) : "memory");
}
__device__ __forceinline__ void st_async1(uint32_t a, uint32_t x, uint32_t bar) {
    asm volatile("st.async.shared::cluster.mbarrier::complete_tx::bytes.b32 [%0], %1, [%2];"
                 ::"r"(a), "r"(x), "r"(bar) : "memory");
}
__device__ __forceinline__ void cons_sync() { asm volatile("bar.sync 1, 256;" ::: "memory"); }

__device__ __forceinline__ uint32_t lds32(uint32_t a) {
    uint32_t v; asm volatile("ld.shared.u32 %0, [%1];" : "=r"(v) : "r"(a) : "memory"); return v;
}
__device__ __forceinline__ uint32_t lds16(uint32_t a) {
    uint32_t v; asm volatile("ld.shared.u16 %0, [%1];" : "=r"(v) : "r"(a) : "memory"); return v;
}
__device__ __forceinline__ float ldsf(uint32_t a) {
    float v; asm volatile("ld.shared.f32 %0, [%1];" : "=f"(v) : "r"(a) : "memory"); return v;
}
__device__ __forceinline__ float2 ldsf2(uint32_t a) {
    float2 v; asm volatile("ld.shared.v2.f32 {%0, %1}, [%2];" : "=f"(v.x), "=f"(v.y) : "r"(a) : "memory"); return v;
}
__device__ __forceinline__ float4 ldsf4(uint32_t a) {
    float4 v; asm volatile("ld.shared.v4.f32 {%0, %1, %2, %3}, [%4];" : "=f"(v.x), "=f"(v.y), "=f"(v.z), "=f"(v.w) : "r"(a) : "memory"); return v;
}
__device__ __forceinline__ uint4 lds128(uint32_t a) {
    uint4 v; asm volatile("ld.shared.v4.u32 {%0, %1, %2, %3}, [%4];" : "=r"(v.x), "=r"(v.y), "=r"(v.z), "=r"(v.w) : "r"(a) : "memory"); return v;
}
__device__ __forceinline__ void sts32(uint32_t a, uint32_t v) { asm volatile("st.shared.u32 [%0], %1;" ::"r"(a), "r"(v) : "memory"); }
__device__ __forceinline__ void stsf2(uint32_t a, float x, float y) { asm volatile("st.shared.v2.f32 [%0], {%1, %2};" ::"r"(a), "f"(x), "f"(y) : "memory"); }
__device__ __forceinline__ void stsf4(uint32_t a, float x, float y, float z, float w) {
    asm volatile("st.shared.v4.f32 [%0], {%1, %2, %3, %4};" ::"r"(a), "f"(x), "f"(y), "f"(z), "f"(w) : "memory");
}
__device__ __forceinline__ uint32_t pack_bf16(float lo, float hi) {
    uint32_t r; asm("cvt.rn.bf16x2.f32 %0, %1, %2;" : "=r"(r) : "f"(hi), "f"(lo)); return r;
}
__device__ __forceinline__ float bf_lo(uint32_t v) { return __uint_as_float(v << 16); }
__device__ __forceinline__ float bf_hi(uint32_t v) { return __uint_as_float(v & 0xffff0000u); }
__device__ __forceinline__ float bf_round(float x) { return __bfloat162float(__float2bfloat16_rn(x)); }

__device__ __forceinline__ void mma16816(float (&c)[4], uint32_t a0, uint32_t a1, uint32_t a2, uint32_t a3, uint32_t b0, uint32_t b1) {
    asm volatile("mma.sync.aligned.m16n8k16.row.col.f32.bf16.bf16.f32 {%0,%1,%2,%3}, {%4,%5,%6,%7}, {%8,%9}, {%0,%1,%2,%3};"
                 : "+f"(c[0]), "+f"(c[1]), "+f"(c[2]), "+f"(c[3])
                 : "r"(a0), "r"(a1), "r"(a2), "r"(a3), "r"(b0), "r"(b1));
}

__device__ __forceinline__ void gemv16(float (&acc)[8][4], uint32_t addr, uint32_t a0, uint32_t a1, uint32_t a2, uint32_t a3) {
    uint32_t b[4][4];
#pragma unroll
    for (int i = 0; i < 4; i++)
        asm volatile("ldmatrix.sync.aligned.m8n8.x4.trans.shared.b16 {%0,%1,%2,%3}, [%4];"
                     : "=r"(b[i][0]), "=r"(b[i][1]), "=r"(b[i][2]), "=r"(b[i][3]) : "r"(addr ^ (i << 5)) : "memory");
#pragma unroll
    for (int i = 0; i < 4; i++) {
        mma16816(acc[2 * i], a0, a1, a2, a3, b[i][0], b[i][1]);
        mma16816(acc[2 * i + 1], a0, a1, a2, a3, b[i][2], b[i][3]);
    }
}
template <int NV>
__device__ __forceinline__ void class_reduce(float (&acc)[8][4]) {
#pragma unroll
    for (int c = 0; c < 4; c++)
#pragma unroll
        for (int j = 0; j < NV; j++) acc[c][j] += __shfl_xor_sync(~0u, acc[c + 4][j], 16);
#pragma unroll
    for (int c = 0; c < 2; c++)
#pragma unroll
        for (int j = 0; j < NV; j++) acc[c][j] += __shfl_xor_sync(~0u, acc[c + 2][j], 8);
#pragma unroll
    for (int j = 0; j < NV; j++) acc[0][j] += __shfl_xor_sync(~0u, acc[1][j], 4);
}
__device__ __forceinline__ void zero_acc(float (&acc)[8][4]) {
#pragma unroll
    for (int c = 0; c < 8; c++)
#pragma unroll
        for (int j = 0; j < 4; j++) acc[c][j] = 0.f;
}

__global__ void __launch_bounds__(NTHR, 1)
fused_decode_kernel(const __grid_constant__ CUtensorMap tmA, const __grid_constant__ CUtensorMap tmB, const __grid_constant__ Params P)
{
    extern __shared__ __align__(1024) char smem_raw[];
    const uint32_t sb = (uint32_t)__cvta_generic_to_shared(smem_raw);
    const uint32_t bars = sb + SM_BAR;
    const int tid = threadIdx.x, warp = tid >> 5, lane = tid & 31;
    const int h = blockIdx.x >> 3, r = blockIdx.x & 7;

    if (warp == 8) {
        uint64_t pol;
        asm volatile("createpolicy.fractional.L2::evict_first.b64 %0, 1.0;" : "=l"(pol));
        const size_t kvoffA = ((size_t)h * SK + (SK - WIN)) * 512 + (size_t)r * TILE;
        const size_t kvoffB = ((size_t)h * SK) * 512 + (size_t)r * TILE;
        if (lane == 0) {
            TRACE(0);
            const CUtensorMap* tm = r < 4 ? &tmA : &tmB;
#pragma unroll
            for (int i = 0; i < NS; i++) mbar_init(bars + (B_FULL + i) * 8, 1);
            mbar_init(bars + B_X * 8, 1);
            asm volatile("fence.proxy.async.shared::cta;" ::: "memory");
            mbar_expect(bars + B_X * 8, 2 * 896);
            bulk_load(sb + SM_X, P.x, 896, bars + B_X * 8, pol);
            bulk_load(sb + SM_GW, P.gw, 896, bars + B_X * 8, pol);
#pragma unroll
            for (int i = 0; i < T_K; i++) {
                mbar_expect(bars + (B_FULL + i) * 8, TILE);
                tensor_load(sb + i * TILE, tm, h * 512 + (r & 3) * 128, i * 64, bars + (B_FULL + i) * 8, pol);
            }
#pragma unroll
            for (int i = T_K; i < NS; i++) {
                mbar_expect(bars + (B_FULL + i) * 8, TILE);
                bulk_load(sb + i * TILE, P.k[0] + kvoffA + (size_t)(i - T_K) * (CL * TILE), TILE, bars + (B_FULL + i) * 8, pol);
            }
#pragma unroll
            for (int i = 0; i < NS; i++) mbar_init(bars + (B_EMPTY + i) * 8, 8);
            mbar_init(bars + B_Q * 8, 1);
            mbar_init(bars + B_STAT * 8, 1);
            mbar_init(bars + B_O * 8, 1);
            mbar_init(bars + (B_O + 1) * 8, 1);
            mbar_expect(bars + B_Q * 8, 2048);
            mbar_expect(bars + B_STAT * 8, 128);
            mbar_expect(bars + B_O * 8, 4096);
            mbar_expect(bars + (B_O + 1) * 8, 4096);
            asm volatile("fence.mbarrier_init.release.cluster;" ::: "memory");
            TRACE(1);
        }
        __syncthreads();
        asm volatile("barrier.cluster.arrive.relaxed.aligned;" ::: "memory");
        if (lane == 0) {
            int slot = 0;
            uint32_t ph = 0;
            auto run = [&](const char* src, int n, uint32_t stride, uint32_t bytes) {
                for (int i = 0; i < n; i++) {
                    mbar_wait(bars + (B_EMPTY + slot) * 8, ph);
                    mbar_expect(bars + (B_FULL + slot) * 8, bytes);
                    bulk_load(sb + slot * TILE, src, bytes, bars + (B_FULL + slot) * 8, pol);
                    src += stride;
                    if (++slot == NS) { slot = 0; ph ^= 1; }
                }
            };
            run(P.k[0] + kvoffA + (size_t)(NS - T_K) * (CL * TILE), T_KB - NS, CL * TILE, TILE);
            run(P.k[1] + kvoffB, 32, CL * TILE, TILE);
            run(P.v[0] + kvoffA, 8, CL * TILE, TILE);
            run(P.v[1] + kvoffB, 32, CL * TILE, TILE);
            run(P.wo[0] + (size_t)(h * 512 + r * 64) * 896, 4, WOTILE, WOTILE);
            run(P.wo[1] + (size_t)(h * 512 + r * 64) * 896, 4, WOTILE, WOTILE);
            TRACE(2);
        }
        __syncwarp();
        asm volatile("barrier.cluster.wait.aligned;" ::: "memory");
        if (blockIdx.x < 56) {
            const uint32_t epoch = lds32(sb + SM_MISC + 4);
            const uint32_t tag = (epoch & 1) ^ 1;
            const uint4* src = reinterpret_cast<const uint4*>(g_part) + blockIdx.x * (NCTA * 2) + lane;
            uint4 v[4];
            int it = 0;
            while (true) {
#pragma unroll
                for (int i = 0; i < 4; i++)
                    asm volatile("ld.relaxed.gpu.global.v4.u32 {%0,%1,%2,%3}, [%4];"
                                 : "=r"(v[i].x), "=r"(v[i].y), "=r"(v[i].z), "=r"(v[i].w) : "l"(src + i * 32) : "memory");
                uint32_t all1 = 1, any1 = 0;
#pragma unroll
                for (int i = 0; i < 4; i++) {
                    all1 &= v[i].x & v[i].y & v[i].z & v[i].w;
                    any1 |= v[i].x | v[i].y | v[i].z | v[i].w;
                }
                const bool ok = tag ? (all1 & 1) : !(any1 & 1);
                if (__all_sync(~0u, ok)) break;
                if (++it > (1 << 20)) __trap();
            }
            float s0 = (__uint_as_float(v[0].x) + __uint_as_float(v[1].x)) + (__uint_as_float(v[2].x) + __uint_as_float(v[3].x));
            float s1 = (__uint_as_float(v[0].y) + __uint_as_float(v[1].y)) + (__uint_as_float(v[2].y) + __uint_as_float(v[3].y));
            float s2 = (__uint_as_float(v[0].z) + __uint_as_float(v[1].z)) + (__uint_as_float(v[2].z) + __uint_as_float(v[3].z));
            float s3 = (__uint_as_float(v[0].w) + __uint_as_float(v[1].w)) + (__uint_as_float(v[2].w) + __uint_as_float(v[3].w));
            const bool b1 = lane & 2, b2 = lane & 4;
            float u0 = (b1 ? s2 : s0) + __shfl_xor_sync(~0u, b1 ? s0 : s2, 2);
            float u1 = (b1 ? s3 : s1) + __shfl_xor_sync(~0u, b1 ? s1 : s3, 2);
            float w = (b2 ? u1 : u0) + __shfl_xor_sync(~0u, b2 ? u0 : u1, 4);
            w += __shfl_xor_sync(~0u, w, 8);
            w += __shfl_xor_sync(~0u, w, 16);
            if (lane < 8) P.out[blockIdx.x * 8 + (lane & 1) * 4 + (lane & 2) + (lane >> 2)] = __float2bfloat16_rn(w);
            if (blockIdx.x == 0 && lane == 0) g_epoch = epoch + 1;
            if (lane == 0) TRACE(3);
        }
        return;
    }

    uint32_t epoch_ld = 0;
    if (tid == 0) asm volatile("ld.relaxed.gpu.global.u32 %0, [%1];" : "=r"(epoch_ld) : "l"(&g_epoch) : "memory");
    const int g = lane >> 2, t = lane & 3;
    const bool act = t == (g >> 1);
    const uint32_t sel0 = act ? ((g & 1) ? 0x1044u : 0x4410u) : 0x4444u;
    const uint32_t sel1 = act ? ((g & 1) ? 0x3244u : 0x4432u) : 0x4444u;
    const int lrow = (lane & 7) + (lane & 8);
    const uint32_t lchunk = (uint32_t)(((lane >> 4) ^ (lane & 7)) << 4);
    float acc[8][4];
    zero_acc(acc);
    __syncthreads();
    asm volatile("barrier.cluster.arrive.relaxed.aligned;" ::: "memory");

    mbar_wait(bars + B_X * 8, 0);
    if (warp == 7) {
        float s = 0.f;
#pragma unroll
        for (int i = 0; i < 7; i++) {
            const uint32_t xv = lds32(sb + SM_X + (i * 32 + lane) * 4), gv = lds32(sb + SM_GW + (i * 32 + lane) * 4);
            s += bf_round(bf_lo(xv) * bf_lo(gv)) + bf_round(bf_hi(xv) * bf_hi(gv));
        }
#pragma unroll
        for (int o = 16; o; o >>= 1) s += __shfl_xor_sync(~0u, s, o);
        s = bf_round(s);
        if (lane == 0) sts32(sb + SM_MISC, __float_as_uint(bf_round(1.f / (1.f + __expf(-s)))));
    }
    {
        const int seg = warp & 1, ks = warp >> 1;
        const uint32_t off = (ks * 16 + lrow) * 256 + seg * 128 + lchunk;
#pragma unroll
        for (int T = 0; T < T_K; T++) {
            const uint32_t xa = lds16(sb + SM_X + (T * 64 + ks * 16 + g) * 2), xb = lds16(sb + SM_X + (T * 64 + ks * 16 + 8 + g) * 2);
            mbar_wait(bars + (B_FULL + T) * 8, 0);
            gemv16(acc, sb + T * TILE + off, __byte_perm(xa, 0, sel0), 0, __byte_perm(xb, 0, sel0), 0);
            __syncwarp();
            if (lane == 0) mbar_arrive(bars + (B_EMPTY + T) * 8, 1);
        }
        if (tid == 0) { sts32(sb + SM_MISC + 4, epoch_ld); TRACE(4); }
        class_reduce<2>(acc);
        stsf2(sb + SM_QRED + (ks * 128 + seg * 64 + 2 * lane) * 4, acc[0][0], acc[0][1]);
        asm volatile("barrier.cluster.wait.aligned;" ::: "memory");
        cons_sync();
        float4 a = ldsf4(sb + SM_QRED + lane * 16);
#pragma unroll
        for (int i = 1; i < 4; i++) {
            const float4 b = ldsf4(sb + SM_QRED + i * 512 + lane * 16);
            a.x += b.x; a.y += b.y; a.z += b.z; a.w += b.w;
        }
        st_async2(mapa(sb + SM_Q + r * 256 + lane * 8, warp), __uint_as_float(pack_bf16(a.x, a.y)), __uint_as_float(pack_bf16(a.z, a.w)),
                  mapa(bars + B_Q * 8, warp));
    }

    {
        mbar_wait_cluster(bars + B_Q * 8, 0);
        if (tid == 0) TRACE(5);
        const uint32_t koff = ((warp & 1) * 16 + g) * 512 + (t + 4 * (g & 1)) * 16;
        const uint32_t qoff = sb + SM_Q + (g & 1) * 512 + (t + 4 * ((g >> 1) & 1)) * 16;
        const uint32_t soff = sb + SM_S + ((warp & 1) * 16 + g + 8 * (t >> 1)) * 8;
        const bool swr = (t & 1) == (g & 1);
        int slot = T_K % NS;
        uint32_t ph = (T_K / NS) & 1;
#pragma unroll 1
        for (int br = 0; br < 2; br++) {
            uint4 q[8];
#pragma unroll
            for (int s = 0; s < 8; s++) q[s] = lds128((qoff + br * 1024) ^ (s << 6));
            const int T0 = br ? T_KB : T_K, T1 = br ? T_V : T_KB;
#pragma unroll 1
            for (int T = T0; T < T1; T++) {
                if ((slot & 3) == (warp >> 1)) {
                    mbar_wait(bars + (B_FULL + slot) * 8, ph);
                    const uint32_t a = sb + slot * TILE + koff;
                    float c[4][4];
#pragma unroll
                    for (int i = 0; i < 4; i++) { c[i][0] = c[i][1] = c[i][2] = c[i][3] = 0.f; }
                    uint4 ka[8], kb[8];
#pragma unroll
                    for (int s = 0; s < 8; s++) { ka[s] = lds128(a ^ (s << 6)); kb[s] = lds128((a + 8 * 512) ^ (s << 6)); }
#pragma unroll
                    for (int s = 0; s < 8; s++) {
                        mma16816(c[(2 * s) & 3], ka[s].x, kb[s].x, ka[s].y, kb[s].y, q[s].x, q[s].y);
                        mma16816(c[(2 * s + 1) & 3], ka[s].z, kb[s].z, ka[s].w, kb[s].w, q[s].z, q[s].w);
                    }
                    __syncwarp();
                    if (lane == 0) mbar_arrive(bars + (B_EMPTY + slot) * 8, 4);
                    const float s0 = (c[0][0] + c[1][0]) + (c[2][0] + c[3][0]), s1 = (c[0][1] + c[1][1]) + (c[2][1] + c[3][1]);
                    const float s2 = (c[0][2] + c[1][2]) + (c[2][2] + c[3][2]), s3 = (c[0][3] + c[1][3]) + (c[2][3] + c[3][3]);
                    if (swr) stsf2(soff + (T - T_K) * 256, (t >> 1) ? s2 : s0, (t >> 1) ? s3 : s1);
                }
                if (++slot == NS) { slot = 0; ph ^= 1; }
            }
        }
    }

    {
        cons_sync();
        if (tid == 0) TRACE(6);
        constexpr float SC = 0.0625f * 1.4426950408889634f;
        float2 s[5];
#pragma unroll
        for (int i = 0; i < 5; i++) { s[i] = ldsf2(sb + SM_S + (i * 256 + tid) * 8); s[i].x *= SC; s[i].y *= SC; }
        float m0 = s[0].x, m1 = s[0].y;
        float m2 = fmaxf(fmaxf(s[1].x, s[2].x), fmaxf(s[3].x, s[4].x)), m3 = fmaxf(fmaxf(s[1].y, s[2].y), fmaxf(s[3].y, s[4].y));
#pragma unroll
        for (int o = 16; o; o >>= 1) {
            m0 = fmaxf(m0, __shfl_xor_sync(~0u, m0, o)); m1 = fmaxf(m1, __shfl_xor_sync(~0u, m1, o));
            m2 = fmaxf(m2, __shfl_xor_sync(~0u, m2, o)); m3 = fmaxf(m3, __shfl_xor_sync(~0u, m3, o));
        }
        if (lane == 0) stsf4(sb + SM_RED + warp * 16, m0, m1, m2, m3);
        cons_sync();
#pragma unroll
        for (int w = 0; w < 8; w++) {
            const float4 v = ldsf4(sb + SM_RED + w * 16);
            m0 = fmaxf(m0, v.x); m1 = fmaxf(m1, v.y); m2 = fmaxf(m2, v.z); m3 = fmaxf(m3, v.w);
        }
        float l0, l1, l2 = 0.f, l3 = 0.f;
        l0 = exp2f(s[0].x - m0); l1 = exp2f(s[0].y - m1);
        sts32(sb + SM_P + tid * 4, pack_bf16(l0, l1));
#pragma unroll
        for (int i = 1; i < 5; i++) {
            const float e0 = exp2f(s[i].x - m2), e1 = exp2f(s[i].y - m3);
            l2 += e0; l3 += e1;
            sts32(sb + SM_P + (i * 256 + tid) * 4, pack_bf16(e0, e1));
        }
#pragma unroll
        for (int o = 16; o; o >>= 1) {
            l0 += __shfl_xor_sync(~0u, l0, o); l1 += __shfl_xor_sync(~0u, l1, o);
            l2 += __shfl_xor_sync(~0u, l2, o); l3 += __shfl_xor_sync(~0u, l3, o);
        }
        if (lane == 0) stsf4(sb + SM_RED + 128 + warp * 16, l0, l1, l2, l3);
        cons_sync();
        if (warp == 0 && lane < 16) {
            const int dest = lane & 7, br = lane >> 3, j = br * 2 + (dest >> 2);
            float l = 0.f;
#pragma unroll
            for (int w = 0; w < 8; w++) l += ldsf(sb + SM_RED + 128 + w * 16 + j * 4);
            const float m = j == 0 ? m0 : j == 1 ? m1 : j == 2 ? m2 : m3;
            st_async2(mapa(sb + SM_STAT + (br * 8 + r) * 8, dest), m, l, mapa(bars + B_STAT * 8, dest));
        }
        if (tid == 0) TRACE(7);
    }

    int slot = T_V % NS;
    uint32_t ph = (T_V / NS) & 1;
    {
        const int kh = warp >> 2, seg = warp & 3;
        const uint32_t voff = (kh * 16 + lrow) * 512 + seg * 128 + lchunk;
        uint32_t pa = sb + SM_P + (kh * 16 + g) * 4;
#pragma unroll 1
        for (int br = 0; br < 2; br++) {
            zero_acc(acc);
            const int n = br ? 32 : 8;
#pragma unroll 1
            for (int i = 0; i < n; i++) {
                const uint32_t wa = lds32(pa), wb = lds32(pa + 32);
                pa += 128;
                mbar_wait(bars + (B_FULL + slot) * 8, ph);
                gemv16(acc, sb + slot * TILE + voff, __byte_perm(wa, 0, sel0), __byte_perm(wa, 0, sel1), __byte_perm(wb, 0, sel0), __byte_perm(wb, 0, sel1));
                __syncwarp();
                if (lane == 0) mbar_arrive(bars + (B_EMPTY + slot) * 8, 1);
                if (++slot == NS) { slot = 0; ph ^= 1; }
            }
            class_reduce<4>(acc);
            const uint32_t dst = sb + SM_OP + ((br * 16 + r * 2 + kh) * OSTR + 2 * lane) * 4;
            st_async2(mapa(dst, seg), acc[0][0], acc[0][1], mapa(bars + (B_O + br) * 8, seg));
            st_async2(mapa(dst, 4 + seg), acc[0][2], acc[0][3], mapa(bars + (B_O + br) * 8, 4 + seg));
        }
        if (tid == 0) TRACE(8);
    }

    {
        mbar_wait_cluster(bars + B_STAT * 8, 0);
        float wgt;
        {
            const float2 ml = ldsf2(sb + SM_STAT + (lane & 15) * 8);
            float M = ml.x;
#pragma unroll
            for (int o = 4; o; o >>= 1) M = fmaxf(M, __shfl_xor_sync(~0u, M, o));
            const float e = exp2f(ml.x - M);
            float L = e * ml.y;
#pragma unroll
            for (int o = 4; o; o >>= 1) L += __shfl_xor_sync(~0u, L, o);
            const float gate = ldsf(sb + SM_MISC);
            wgt = ((lane & 8) ? bf_round(1.f - gate) : gate) * e / L;
        }
        zero_acc(acc);
        const uint32_t ooff = lrow * 896 + warp * 128 + lchunk;
        const int vi = tid >> 2;
#pragma unroll 1
        for (int br = 0; br < 2; br++) {
            float w4[4];
#pragma unroll
            for (int k = 0; k < 4; k++) w4[k] = __shfl_sync(~0u, wgt, br * 8 + ((t + 4 * k) >> 1));
            mbar_wait_cluster(bars + (B_O + br) * 8, 0);
            float o = 0.f;
#pragma unroll
            for (int k = 0; k < 4; k++) o += w4[k] * ldsf(sb + SM_OP + ((br * 16 + t + 4 * k) * OSTR + vi) * 4);
            o += __shfl_xor_sync(~0u, o, 1);
            o += __shfl_xor_sync(~0u, o, 2);
            if (t == 0) {
                const float hi = bf_round(o);
                sts32(sb + SM_OV + (br * 64 + vi) * 4, pack_bf16(hi, o - hi));
            }
            cons_sync();
            if (tid == 0) TRACE(9 + br);
            if (warp < 7) {
#pragma unroll
                for (int i = 0; i < 4; i++) {
                    const uint32_t wa = lds32(sb + SM_OV + (br * 64 + i * 16 + g) * 4), wb = lds32(sb + SM_OV + (br * 64 + i * 16 + 8 + g) * 4);
                    mbar_wait(bars + (B_FULL + slot) * 8, ph);
                    gemv16(acc, sb + slot * TILE + ooff, __byte_perm(wa, 0, sel0), __byte_perm(wa, 0, sel1), __byte_perm(wb, 0, sel0), __byte_perm(wb, 0, sel1));
                    if (NS < 8) { __syncwarp(); if (lane == 0) mbar_arrive(bars + (B_EMPTY + slot) * 8, warp == 0 ? 2 : 1); }
                    if (++slot == NS) { slot = 0; ph ^= 1; }
                }
            }
        }
        if (warp < 7) {
            if (tid == 0) TRACE(11);
#pragma unroll
            for (int c = 0; c < 8; c++) { acc[c][0] += acc[c][2]; acc[c][1] += acc[c][3]; }
            class_reduce<2>(acc);
            const uint32_t tag = (lds32(sb + SM_MISC + 4) & 1) ^ 1;
            const uint32_t v0 = (__float_as_uint(acc[0][0]) & ~1u) | tag, v1 = (__float_as_uint(acc[0][1]) & ~1u) | tag;
            uint32_t* dst = g_part + ((warp * 8 + g) * NCTA + blockIdx.x) * 8 + 2 * t;
            asm volatile("st.relaxed.gpu.global.v2.u32 [%0], {%1, %2};" ::"l"(dst), "r"(v0), "r"(v1) : "memory");
            if (tid == 0) TRACE(12);
        }
    }
}

typedef CUresult (*EncodeFn)(CUtensorMap*, CUtensorMapDataType, cuuint32_t, void*, const cuuint64_t*, const cuuint64_t*,
                             const cuuint32_t*, const cuuint32_t*, CUtensorMapInterleave, CUtensorMapSwizzle,
                             CUtensorMapL2promotion, CUtensorMapFloatOOBfill);

}

extern "C" void kernel_launch(void* const* d_in, const int* in_sizes, int n_in, void* d_out, int out_size) {
    (void)in_sizes; (void)n_in; (void)out_size;
    static EncodeFn encode = nullptr;
    if (!encode) {
        cudaDriverEntryPointQueryResult qr;
        cudaGetDriverEntryPoint("cuTensorMapEncodeTiled", (void**)&encode, cudaEnableDefault, &qr);
        cudaFuncSetAttribute(fused_decode_kernel, cudaFuncAttributeMaxDynamicSharedMemorySize, SM_TOTAL);
    }
    CUtensorMap tm[2];
    for (int b = 0; b < 2; b++) {
        cuuint64_t dims[2] = {4096, D_MODEL}, strides[1] = {8192};
        cuuint32_t box[2] = {128, 64}, es[2] = {1, 1};
        encode(&tm[b], CU_TENSOR_MAP_DATA_TYPE_BFLOAT16, 2, d_in[b ? 8 : 3], dims, strides, box, es,
               CU_TENSOR_MAP_INTERLEAVE_NONE, CU_TENSOR_MAP_SWIZZLE_NONE, CU_TENSOR_MAP_L2_PROMOTION_NONE,
               CU_TENSOR_MAP_FLOAT_OOB_FILL_NONE);
    }
    Params p;
    p.x = (const char*)d_in[0]; p.gw = (const char*)d_in[10];
    p.k[0] = (const char*)d_in[1]; p.v[0] = (const char*)d_in[2]; p.wo[0] = (const char*)d_in[4];
    p.k[1] = (const char*)d_in[6]; p.v[1] = (const char*)d_in[7]; p.wo[1] = (const char*)d_in[9];
    p.out = (__nv_bfloat16*)d_out;

    cudaLaunchConfig_t cfg = {};
    cfg.gridDim = dim3(NCTA);
    cfg.blockDim = dim3(NTHR);
    cfg.dynamicSmemBytes = SM_TOTAL;
    cfg.stream = cudaStreamPerThread;
    cudaLaunchAttribute at[1];
    at[0].id = cudaLaunchAttributeClusterDimension;
    at[0].val.clusterDim.x = CL; at[0].val.clusterDim.y = 1; at[0].val.clusterDim.z = 1;
    cfg.attrs = at;
    cfg.numAttrs = 1;
    cudaLaunchKernelEx(&cfg, fused_decode_kernel, tm[0], tm[1], p);
}
```

```cpp
#include <cuda_runtime.h>
#include <cuda_bf16.h>
#include <cuda.h>
#include <stdint.h>

namespace {

constexpr int D_MODEL = 448;
constexpr int SK      = 8192;
constexpr int WIN     = 2048;
constexpr int NCTA    = 64;
constexpr int CL      = 8;
constexpr int NTHR    = 288;
#define NSLOT 12
#define KFIRST 1
#define TAU 328
#define TAUO (TAU * 7 / 8)
#define LEAD 3
#define NINIT 8
constexpr int NS      = NSLOT;
constexpr int TILE    = 16384;
constexpr int T_K = 7, T_KB = 15, T_V = 47, T_VB = 55, T_O = 87, T_END = 95;
constexpr int OSTR = 72;

constexpr int SM_RING  = 0;
constexpr int SM_Q     = SM_RING + NS * TILE;
constexpr int SM_X     = SM_Q + 2048;
constexpr int SM_GW    = SM_X + 896;
constexpr int SM_QRED  = SM_GW + 896;
constexpr int SM_S     = SM_QRED + 2048;
constexpr int SM_P     = SM_S + 10240;
constexpr int SM_OP    = SM_P + 5120;
constexpr int SM_STAT  = SM_OP + 2 * 16 * OSTR * 4;
constexpr int SM_RED   = SM_STAT + 128;
constexpr int SM_FIN   = SM_QRED;
constexpr int SM_MISC  = SM_RED + 256;
constexpr int SM_BAR   = SM_MISC + 16;
constexpr int B_FULL = 0, B_EMPTY = NS, B_X = 2 * NS, B_Q = B_X + 1, B_STAT = B_X + 2, B_O = B_X + 3;
constexpr int B_FIN = B_O + 2, B_WO = B_FIN + 1;
constexpr int NBAR     = B_WO + 8;
static_assert(NS >= 8 && NS % 2 == 0, "ring size");
constexpr int SM_TOTAL = SM_BAR + NBAR * 8;

struct Params {
    const char* x; const char* gw;
    const char* k[2]; const char* v[2];
    __nv_bfloat16* out;
    uint32_t* ox; uint32_t* epoch;
};

__device__ __align__(128) uint32_t g_ox[8 * 1024];
__device__ uint32_t g_epoch;
#define TRACE(i) do {} while (0)
#define TRACE_DEP(i, v) do {} while (0)
#define TRACE_DUMP() do {} while (0)
#define TRACE_START() do {} while (0)
constexpr int SM_EXTRA = 0;

__device__ __forceinline__ void mbar_init(uint32_t a, uint32_t c) {
    asm volatile("mbarrier.init.shared::cta.b64 [%0], %1;" ::"r"(a), "r"(c) : "memory");
}
__device__ __forceinline__ void mbar_expect(uint32_t a, uint32_t bytes) {
    asm volatile("mbarrier.arrive.expect_tx.shared::cta.b64 _, [%0], %1;" ::"r"(a), "r"(bytes) : "memory");
}
__device__ __forceinline__ void mbar_arrive(uint32_t a, uint32_t cnt) {
    asm volatile("mbarrier.arrive.shared::cta.b64 _, [%0], %1;" ::"r"(a), "r"(cnt) : "memory");
}
__device__ __forceinline__ void mbar_wait(uint32_t a, uint32_t parity) {
    uint32_t ok;
    int it = 0;
    do {
        asm volatile("{.reg .pred p; mbarrier.try_wait.parity.shared::cta.b64 p, [%1], %2; selp.u32 %0, 1, 0, p;}"
                     : "=r"(ok) : "r"(a), "r"(parity) : "memory");
        if (++it > (1 << 22)) __trap();
    } while (!ok);
}
__device__ __forceinline__ uint32_t mbar_test(uint32_t a, uint32_t parity) {
    uint32_t ok;
    asm volatile("{.reg .pred p; mbarrier.test_wait.parity.shared::cta.b64 p, [%1], %2; selp.u32 %0, 1, 0, p;}"
                 : "=r"(ok) : "r"(a), "r"(parity) : "memory");
    return ok;
}
__device__ __forceinline__ void mbar_wait_cluster(uint32_t a, uint32_t parity) {
    uint32_t ok;
    int it = 0;
    do {
        asm volatile("{.reg .pred p; mbarrier.try_wait.parity.acquire.cluster.shared::cta.b64 p, [%1], %2; selp.u32 %0, 1, 0, p;}"
                     : "=r"(ok) : "r"(a), "r"(parity) : "memory");
        if (++it > (1 << 22)) __trap();
    } while (!ok);
}
__device__ __forceinline__ void bulk_load(uint32_t dst, const void* src, uint32_t bytes, uint32_t bar, uint64_t pol) {
    asm volatile("cp.async.bulk.shared::cluster.global.mbarrier::complete_tx::bytes.L2::cache_hint [%0], [%1], %2, [%3], %4;"
                 ::"r"(dst), "l"(src), "r"(bytes), "r"(bar), "l"(pol) : "memory");
}
__device__ __forceinline__ void tensor_load(uint32_t dst, const CUtensorMap* tm, int c0, int c1, uint32_t bar, uint64_t pol) {
    asm volatile("cp.async.bulk.tensor.2d.shared::cluster.global.mbarrier::complete_tx::bytes.L2::cache_hint [%0], [%1, {%3, %4}], [%2], %5;"
                 ::"r"(dst), "l"(tm), "r"(bar), "r"(c0), "r"(c1), "l"(pol) : "memory");
}
__device__ __forceinline__ uint32_t mapa(uint32_t a, uint32_t rank) {
    uint32_t r;
    asm("mapa.shared::cluster.u32 %0, %1, %2;" : "=r"(r) : "r"(a), "r"(rank));
    return r;
}
__device__ __forceinline__ void st_async2(uint32_t a, float x, float y, uint32_t bar) {
    asm volatile("st.async.shared::cluster.mbarrier::complete_tx::bytes.v2.f32 [%0], {%1, %2}, [%3];"
                 ::"r"(a), "f"(x), "f"(y), "r"(bar) : "memory");
}
__device__ __forceinline__ void st_async1(uint32_t a, uint32_t x, uint32_t bar) {
    asm volatile("st.async.shared::cluster.mbarrier::complete_tx::bytes.b32 [%0], %1, [%2];"
                 ::"r"(a), "r"(x), "r"(bar) : "memory");
}
__device__ __forceinline__ bool elect_one() {
    uint32_t p;
    asm volatile("{.reg .pred P; elect.sync _|P, 0xffffffff; selp.u32 %0, 1, 0, P;}" : "=r"(p));
    return p;
}
__device__ __forceinline__ void cons_sync() { asm volatile("bar.sync 1, 256;" ::: "memory"); }

__device__ __forceinline__ uint32_t lds32(uint32_t a) {
    uint32_t v; asm volatile("ld.shared.u32 %0, [%1];" : "=r"(v) : "r"(a) : "memory"); return v;
}
__device__ __forceinline__ uint32_t lds16(uint32_t a) {
    uint32_t v; asm volatile("ld.shared.u16 %0, [%1];" : "=r"(v) : "r"(a) : "memory"); return v;
}
__device__ __forceinline__ float ldsf(uint32_t a) {
    float v; asm volatile("ld.shared.f32 %0, [%1];" : "=f"(v) : "r"(a) : "memory"); return v;
}
__device__ __forceinline__ float2 ldsf2(uint32_t a) {
    float2 v; asm volatile("ld.shared.v2.f32 {%0, %1}, [%2];" : "=f"(v.x), "=f"(v.y) : "r"(a) : "memory"); return v;
}
__device__ __forceinline__ float4 ldsf4(uint32_t a) {
    float4 v; asm volatile("ld.shared.v4.f32 {%0, %1, %2, %3}, [%4];" : "=f"(v.x), "=f"(v.y), "=f"(v.z), "=f"(v.w) : "r"(a) : "memory"); return v;
}
__device__ __forceinline__ uint4 lds128(uint32_t a) {
    uint4 v; asm volatile("ld.shared.v4.u32 {%0, %1, %2, %3}, [%4];" : "=r"(v.x), "=r"(v.y), "=r"(v.z), "=r"(v.w) : "r"(a) : "memory"); return v;
}
__device__ __forceinline__ void sts32(uint32_t a, uint32_t v) { asm volatile("st.shared.u32 [%0], %1;" ::"r"(a), "r"(v) : "memory"); }
__device__ __forceinline__ void stsf2(uint32_t a, float x, float y) { asm volatile("st.shared.v2.f32 [%0], {%1, %2};" ::"r"(a), "f"(x), "f"(y) : "memory"); }
__device__ __forceinline__ void stsf4(uint32_t a, float x, float y, float z, float w) {
    asm volatile("st.shared.v4.f32 [%0], {%1, %2, %3, %4};" ::"r"(a), "f"(x), "f"(y), "f"(z), "f"(w) : "memory");
}
__device__ __forceinline__ uint32_t pack_bf16(float lo, float hi) {
    uint32_t r; asm("cvt.rn.bf16x2.f32 %0, %1, %2;" : "=r"(r) : "f"(hi), "f"(lo)); return r;
}
__device__ __forceinline__ float sel(bool p, float a, float b) {
    float r; asm("{.reg .pred q; setp.ne.u32 q, %3, 0; selp.f32 %0, %1, %2, q;}" : "=f"(r) : "f"(a), "f"(b), "r"((uint32_t)p)); return r;
}
__device__ __forceinline__ float bf_lo(uint32_t v) { return __uint_as_float(v << 16); }
__device__ __forceinline__ float bf_hi(uint32_t v) { return __uint_as_float(v & 0xffff0000u); }
__device__ __forceinline__ float bf_round(float x) { return __bfloat162float(__float2bfloat16_rn(x)); }

__device__ __forceinline__ void mma16816(float (&c)[4], uint32_t a0, uint32_t a1, uint32_t a2, uint32_t a3, uint32_t b0, uint32_t b1) {
    asm volatile("mma.sync.aligned.m16n8k16.row.col.f32.bf16.bf16.f32 {%0,%1,%2,%3}, {%4,%5,%6,%7}, {%8,%9}, {%0,%1,%2,%3};"
                 : "+f"(c[0]), "+f"(c[1]), "+f"(c[2]), "+f"(c[3])
                 : "r"(a0), "r"(a1), "r"(a2), "r"(a3), "r"(b0), "r"(b1));
}

__device__ __forceinline__ void gemv16(float (&acc)[8][4], uint32_t addr, uint32_t a0, uint32_t a1, uint32_t a2, uint32_t a3) {
    uint32_t b[4][4];
#pragma unroll
    for (int i = 0; i < 4; i++)
        asm volatile("ldmatrix.sync.aligned.m8n8.x4.trans.shared.b16 {%0,%1,%2,%3}, [%4];"
                     : "=r"(b[i][0]), "=r"(b[i][1]), "=r"(b[i][2]), "=r"(b[i][3]) : "r"(addr ^ (i << 5)) : "memory");
#pragma unroll
    for (int i = 0; i < 4; i++) {
        mma16816(acc[2 * i], a0, a1, a2, a3, b[i][0], b[i][1]);
        mma16816(acc[2 * i + 1], a0, a1, a2, a3, b[i][2], b[i][3]);
    }
}
template <int NV>
__device__ __forceinline__ void class_reduce(float (&acc)[8][4]) {
#pragma unroll
    for (int c = 0; c < 4; c++)
#pragma unroll
        for (int j = 0; j < NV; j++) acc[c][j] += __shfl_xor_sync(~0u, acc[c + 4][j], 16);
#pragma unroll
    for (int c = 0; c < 2; c++)
#pragma unroll
        for (int j = 0; j < NV; j++) acc[c][j] += __shfl_xor_sync(~0u, acc[c + 2][j], 8);
#pragma unroll
    for (int j = 0; j < NV; j++) acc[0][j] += __shfl_xor_sync(~0u, acc[1][j], 4);
}
__device__ __forceinline__ void zero_acc(float (&acc)[8][4]) {
#pragma unroll
    for (int c = 0; c < 8; c++)
#pragma unroll
        for (int j = 0; j < 4; j++) acc[c][j] = 0.f;
}

__global__ void __cluster_dims__(CL, 1, 1) __launch_bounds__(NTHR, 1)
fused_decode_kernel(const __grid_constant__ Params P, const __grid_constant__ CUtensorMap tmA, const __grid_constant__ CUtensorMap tmB,
                    const __grid_constant__ CUtensorMap toA, const __grid_constant__ CUtensorMap toB)
{
    extern __shared__ __align__(1024) char smem_raw[];
    uint32_t sb;
    asm volatile("mov.u32 %0, %1;" : "=r"(sb) : "r"((uint32_t)__cvta_generic_to_shared(smem_raw)));
    const uint32_t bars = sb + SM_BAR;
    int tid, cta;
    asm volatile("mov.u32 %0, %%tid.x;" : "=r"(tid));
    asm volatile("mov.u32 %0, %%ctaid.x;" : "=r"(cta));
    const int warp = tid >> 5, lane = tid & 31;
    const int h = cta >> 3, r = cta & 7;

    if (warp == 8) {
        uint64_t pol;
        asm volatile("createpolicy.fractional.L2::evict_first.b64 %0, 1.0;" : "=l"(pol));
        const size_t kvoffA = ((size_t)h * SK + (SK - WIN)) * 512 + (size_t)r * TILE;
        const size_t kvoffB = ((size_t)h * SK) * 512 + (size_t)r * TILE;
        const CUtensorMap* tm = r < 4 ? &tmA : &tmB;
        auto issue0 = [&](int i) {
            const int T = i < KFIRST ? T_K + i : i < KFIRST + T_K ? i - KFIRST : i;
            mbar_expect(bars + (B_FULL + T) * 8, TILE);
            if (T < T_K) tensor_load(sb + T * TILE, tm, h * 512 + (r & 3) * 128, T * 64, bars + (B_FULL + T) * 8, pol);
            else bulk_load(sb + T * TILE, P.k[0] + kvoffA + (size_t)(T - T_K) * (CL * TILE), TILE, bars + (B_FULL + T) * 8, pol);
        };
        uint32_t t0;
        asm volatile("mov.u32 %0, %%globaltimer_lo;" : "=r"(t0));
        if (elect_one()) {
            TRACE_START();
            asm volatile("prefetch.tensormap [%0];" ::"l"(tm) : "memory");
#pragma unroll
            for (int i = 0; i < NS; i++) mbar_init(bars + (B_FULL + i) * 8, 1);
            mbar_init(bars + B_X * 8, 1);
            asm volatile("fence.mbarrier_init.release.cluster;" ::: "memory");
#pragma unroll
            for (int i = 0; i < KFIRST; i++) issue0(i);
            mbar_expect(bars + B_X * 8, 2 * 896);
            bulk_load(sb + SM_X, P.x, 896, bars + B_X * 8, pol);
            bulk_load(sb + SM_GW, P.gw, 896, bars + B_X * 8, pol);
#pragma unroll
            for (int i = KFIRST; i < NINIT; i++) issue0(i);
#pragma unroll
            for (int i = 0; i < NS; i++) mbar_init(bars + (B_EMPTY + i) * 8, 8);
            mbar_init(bars + B_Q * 8, 1);
            mbar_init(bars + B_STAT * 8, 1);
            mbar_init(bars + B_O * 8, 1);
            mbar_init(bars + (B_O + 1) * 8, 1);
            mbar_init(bars + B_FIN * 8, 1);
#pragma unroll
            for (int i = 0; i < 8; i++) mbar_init(bars + (B_WO + i) * 8, 1);
            mbar_expect(bars + B_Q * 8, 2048);
            mbar_expect(bars + B_STAT * 8, 128);
            mbar_expect(bars + B_O * 8, 4096);
            mbar_expect(bars + (B_O + 1) * 8, 4096);
            mbar_expect(bars + B_FIN * 8, 2048);
            asm volatile("fence.mbarrier_init.release.cluster;" ::: "memory");
            TRACE(1);
        }
        __syncthreads();
        asm volatile("barrier.cluster.arrive.relaxed.aligned;" ::: "memory");
        if (elect_one()) {
            uint32_t due = t0 + (NINIT - LEAD) * TAU;
            auto pace = [&](uint32_t dt) {
                uint32_t now;
                int it = 0;
                do { asm volatile("mov.u32 %0, %%globaltimer_lo;" : "=r"(now)); } while ((int)(now - due) < 0 && ++it < 256);
                due += dt;
            };
#pragma unroll
            for (int i = NINIT; i < NS; i++) { pace(TAU); issue0(i); }
            int slot = 0;
            uint32_t ph = 0;
            auto run = [&](const char* src, int n) {
#pragma unroll 1
                for (int i = 0; i < n; i++) {
                    pace(TAU);
                    mbar_wait(bars + (B_EMPTY + slot) * 8, ph);
                    mbar_expect(bars + (B_FULL + slot) * 8, TILE);
                    bulk_load(sb + slot * TILE, src, TILE, bars + (B_FULL + slot) * 8, pol);
                    src += CL * TILE;
                    if (++slot == NS) { slot = 0; ph ^= 1; }
                }
            };
            run(P.k[0] + kvoffA + (size_t)(NS - T_K) * (CL * TILE), T_KB - NS);
            run(P.k[1] + kvoffB, 32);
            run(P.v[0] + kvoffA, 8);
            asm volatile("prefetch.tensormap [%0];" ::"l"(&toA) : "memory");
            asm volatile("prefetch.tensormap [%0];" ::"l"(&toB) : "memory");
            run(P.v[1] + kvoffB, 32);
            if (h < 7) {
#pragma unroll
                for (int i = 0; i < 8; i++) {
                    const int T = T_O + i;
                    pace(TAUO);
                    mbar_wait(bars + (B_EMPTY + T % NS) * 8, ((T / NS) & 1) ^ 1);
                    mbar_expect(bars + (B_WO + i) * 8, TILE);
                    tensor_load(sb + (T % NS) * TILE, i < 4 ? &toA : &toB, h * 64, r * 512 + (i & 3) * 128, bars + (B_WO + i) * 8, pol);
                }
            }
            TRACE(2);
        }
        __syncwarp();
        asm volatile("barrier.cluster.wait.aligned;" ::: "memory");
        if (h < 7) {
            __nv_bfloat16* outp = P.out + h * 64 + r * 8 + (lane & 7);
            uint32_t* epochp = P.epoch;
            const uint32_t epoch = lds32(sb + SM_MISC + 4);
            mbar_wait_cluster(bars + B_FIN * 8, 0);
            if (lane == 0) TRACE(26);
            float v[16];
#pragma unroll
            for (int i = 0; i < 16; i++) v[i] = ldsf(sb + SM_FIN + (i * 32 + lane) * 4);
            float w = (((v[0] + v[1]) + (v[2] + v[3])) + ((v[4] + v[5]) + (v[6] + v[7]))) +
                      (((v[8] + v[9]) + (v[10] + v[11])) + ((v[12] + v[13]) + (v[14] + v[15])));
            w += __shfl_xor_sync(~0u, w, 8);
            w += __shfl_xor_sync(~0u, w, 16);
            if (lane < 8) *outp = __float2bfloat16_rn(w);
            if (cta == 0 && lane == 0) *epochp = epoch + 1;
            if (lane == 0) TRACE(3);
        }
        TRACE_DUMP();
        return;
    }

    uint32_t epoch_ld = 0;
    if (tid == 0) asm volatile("ld.relaxed.gpu.global.u32 %0, [%1];" : "=r"(epoch_ld) : "l"(P.epoch) : "memory");
    const int g = lane >> 2, t = lane & 3;
    const bool act = t == (g >> 1);
    const uint32_t sel0 = act ? ((g & 1) ? 0x1044u : 0x4410u) : 0x4444u;
    const uint32_t sel1 = act ? ((g & 1) ? 0x3244u : 0x4432u) : 0x4444u;
    const int lrow = (lane & 7) + (lane & 8);
    const uint32_t lchunk = (uint32_t)(((lane >> 4) ^ (lane & 7)) << 4);
    float acc[8][4];
    zero_acc(acc);
    __syncthreads();
    asm volatile("barrier.cluster.arrive.relaxed.aligned;" ::: "memory");

    mbar_wait(bars + B_X * 8, 0);
    if (warp == 7) {
        float s = 0.f;
#pragma unroll
        for (int i = 0; i < 7; i++) {
            const uint32_t xv = lds32(sb + SM_X + (i * 32 + lane) * 4), gv = lds32(sb + SM_GW + (i * 32 + lane) * 4);
            s += bf_round(bf_lo(xv) * bf_lo(gv)) + bf_round(bf_hi(xv) * bf_hi(gv));
        }
#pragma unroll
        for (int o = 16; o; o >>= 1) s += __shfl_xor_sync(~0u, s, o);
        s = bf_round(s);
        if (lane == 0) sts32(sb + SM_MISC, __float_as_uint(bf_round(1.f / (1.f + __expf(-s)))));
    }
    {
        const int seg = warp & 1, ks = warp >> 1;
        const uint32_t off = (ks * 16 + lrow) * 256 + seg * 128 + lchunk;
#pragma unroll
        for (int T = 0; T < T_K; T++) {
            const uint32_t xa = lds16(sb + SM_X + (T * 64 + ks * 16 + g) * 2), xb = lds16(sb + SM_X + (T * 64 + ks * 16 + 8 + g) * 2);
            mbar_wait(bars + (B_FULL + T) * 8, 0);
            gemv16(acc, sb + T * TILE + off, __byte_perm(xa, 0, sel0), 0, __byte_perm(xb, 0, sel0), 0);
            __syncwarp();
            if (lane == 0) mbar_arrive(bars + (B_EMPTY + T) * 8, 1);
        }
        if (tid == 0) { sts32(sb + SM_MISC + 4, epoch_ld); TRACE(4); }
        class_reduce<2>(acc);
        stsf2(sb + SM_QRED + (ks * 128 + seg * 64 + 2 * lane) * 4, acc[0][0], acc[0][1]);
        asm volatile("barrier.cluster.wait.aligned;" ::: "memory");
        cons_sync();
        float4 a = ldsf4(sb + SM_QRED + lane * 16);
#pragma unroll
        for (int i = 1; i < 4; i++) {
            const float4 b = ldsf4(sb + SM_QRED + i * 512 + lane * 16);
            a.x += b.x; a.y += b.y; a.z += b.z; a.w += b.w;
        }
        st_async2(mapa(sb + SM_Q + r * 256 + lane * 8, warp), __uint_as_float(pack_bf16(a.x, a.y)), __uint_as_float(pack_bf16(a.z, a.w)),
                  mapa(bars + B_Q * 8, warp));
    }

    {
        mbar_wait_cluster(bars + B_Q * 8, 0);
        if (tid == 0) TRACE(5);
        const uint32_t koff = ((warp & 1) * 16 + g) * 512 + (t + 4 * (g & 1)) * 16;
        const uint32_t qoff = sb + SM_Q + (g & 1) * 512 + (t + 4 * ((g >> 1) & 1)) * 16;
        const uint32_t soff = sb + SM_S + ((warp & 1) * 16 + g + 8 * (t >> 1)) * 8;
        const bool swr = (t & 1) == (g & 1);
        int slot = T_K % NS;
        uint32_t ph = (T_K / NS) & 1;
#pragma unroll 1
        for (int br = 0; br < 2; br++) {
            uint4 q[8];
#pragma unroll
            for (int s = 0; s < 8; s++) q[s] = lds128((qoff + br * 1024) ^ (s << 6));
            const int T0 = br ? T_KB : T_K, T1 = br ? T_V : T_KB;
#pragma unroll 1
            for (int T = T0; T < T1; T++) {
                if ((slot & 3) == (warp >> 1)) {
                    mbar_wait(bars + (B_FULL + slot) * 8, ph);
                    const uint32_t a = sb + slot * TILE + koff;
                    float c[4][4];
#pragma unroll
                    for (int i = 0; i < 4; i++) { c[i][0] = c[i][1] = c[i][2] = c[i][3] = 0.f; }
                    uint4 ka[8], kb[8];
#pragma unroll
                    for (int s = 0; s < 8; s++) { ka[s] = lds128(a ^ (s << 6)); kb[s] = lds128((a + 8 * 512) ^ (s << 6)); }
#pragma unroll
                    for (int s = 0; s < 8; s++) {
                        mma16816(c[(2 * s) & 3], ka[s].x, kb[s].x, ka[s].y, kb[s].y, q[s].x, q[s].y);
                        mma16816(c[(2 * s + 1) & 3], ka[s].z, kb[s].z, ka[s].w, kb[s].w, q[s].z, q[s].w);
                    }
                    __syncwarp();
                    if (lane == 0) mbar_arrive(bars + (B_EMPTY + slot) * 8, 4);
                    const float s0 = (c[0][0] + c[1][0]) + (c[2][0] + c[3][0]), s1 = (c[0][1] + c[1][1]) + (c[2][1] + c[3][1]);
                    const float s2 = (c[0][2] + c[1][2]) + (c[2][2] + c[3][2]), s3 = (c[0][3] + c[1][3]) + (c[2][3] + c[3][3]);
                    if (swr) stsf2(soff + (T - T_K) * 256, (t >> 1) ? s2 : s0, (t >> 1) ? s3 : s1);
                }
                if (++slot == NS) { slot = 0; ph ^= 1; }
            }
        }
    }

    {
        cons_sync();
        if (tid == 0) TRACE(6);
        constexpr float SC = 0.0625f * 1.4426950408889634f;
        float2 s[5];
#pragma unroll
        for (int i = 0; i < 5; i++) { s[i] = ldsf2(sb + SM_S + (i * 256 + tid) * 8); s[i].x *= SC; s[i].y *= SC; }
        float m0 = s[0].x, m1 = s[0].y;
        float m2 = fmaxf(fmaxf(s[1].x, s[2].x), fmaxf(s[3].x, s[4].x)), m3 = fmaxf(fmaxf(s[1].y, s[2].y), fmaxf(s[3].y, s[4].y));
#pragma unroll
        for (int o = 16; o; o >>= 1) {
            m0 = fmaxf(m0, __shfl_xor_sync(~0u, m0, o)); m1 = fmaxf(m1, __shfl_xor_sync(~0u, m1, o));
            m2 = fmaxf(m2, __shfl_xor_sync(~0u, m2, o)); m3 = fmaxf(m3, __shfl_xor_sync(~0u, m3, o));
        }
        if (lane == 0) stsf4(sb + SM_RED + warp * 16, m0, m1, m2, m3);
        cons_sync();
#pragma unroll
        for (int w = 0; w < 8; w++) {
            const float4 v = ldsf4(sb + SM_RED + w * 16);
            m0 = fmaxf(m0, v.x); m1 = fmaxf(m1, v.y); m2 = fmaxf(m2, v.z); m3 = fmaxf(m3, v.w);
        }
        float l0, l1, l2 = 0.f, l3 = 0.f;
        l0 = exp2f(s[0].x - m0); l1 = exp2f(s[0].y - m1);
        sts32(sb + SM_P + tid * 4, pack_bf16(l0, l1));
#pragma unroll
        for (int i = 1; i < 5; i++) {
            const float e0 = exp2f(s[i].x - m2), e1 = exp2f(s[i].y - m3);
            l2 += e0; l3 += e1;
            sts32(sb + SM_P + (i * 256 + tid) * 4, pack_bf16(e0, e1));
        }
#pragma unroll
        for (int o = 16; o; o >>= 1) {
            l0 += __shfl_xor_sync(~0u, l0, o); l1 += __shfl_xor_sync(~0u, l1, o);
            l2 += __shfl_xor_sync(~0u, l2, o); l3 += __shfl_xor_sync(~0u, l3, o);
        }
        if (lane == 0) stsf4(sb + SM_RED + 128 + warp * 16, l0, l1, l2, l3);
        cons_sync();
        if (warp == 0 && lane < 16) {
            const int dest = lane & 7, br = lane >> 3, j = br * 2 + (dest >> 2);
            float l = 0.f;
#pragma unroll
            for (int w = 0; w < 8; w++) l += ldsf(sb + SM_RED + 128 + w * 16 + j * 4);
            const float m = j == 0 ? m0 : j == 1 ? m1 : j == 2 ? m2 : m3;
            st_async2(mapa(sb + SM_STAT + (br * 8 + r) * 8, dest), m, l, mapa(bars + B_STAT * 8, dest));
        }
        if (tid == 0) TRACE(7);
    }

    const uint32_t tag = ((lds32(sb + SM_MISC + 4) & 1) ^ 1) << 16;
    float wgt;
    auto combine = [&](int br) {
        const int vi = tid >> 2;
        uint32_t* dst = P.ox + ((h * 128 + r * 16 + (vi >> 2)) * 2 + br) * 4 + (vi & 3);
        float w4[4];
#pragma unroll
        for (int k = 0; k < 4; k++) w4[k] = __shfl_sync(~0u, wgt, br * 8 + ((t + 4 * k) >> 1));
        mbar_wait_cluster(bars + (B_O + br) * 8, 0);
        if (tid == 128 && br) TRACE(14);
        float p4[4];
#pragma unroll
        for (int k = 0; k < 4; k++) p4[k] = ldsf(sb + SM_OP + ((br * 16 + t + 4 * k) * OSTR + vi) * 4);
        float o = (w4[0] * p4[0] + w4[1] * p4[1]) + (w4[2] * p4[2] + w4[3] * p4[3]);
        o += __shfl_xor_sync(~0u, o, 1);
        o += __shfl_xor_sync(~0u, o, 2);
        const uint32_t hi = pack_bf16(o, 0.f);
        const uint32_t word = (pack_bf16(o, o - bf_lo(hi)) & ~0x10000u) | tag;
        if (t == 0) asm volatile("st.relaxed.gpu.global.u32 [%0], %1;" ::"l"(dst), "r"(word) : "memory");
    };
    const uint4* oxp = reinterpret_cast<const uint4*>(P.ox) + (r * 128 + warp * 4 + t) * 2;
    auto fetch_o = [&](uint4 (&u)[4], int br) {
#pragma unroll
        for (int j = 0; j < 4; j++)
            asm volatile("ld.relaxed.gpu.global.v4.u32 {%0,%1,%2,%3}, [%4];"
                         : "=r"(u[j].x), "=r"(u[j].y), "=r"(u[j].z), "=r"(u[j].w) : "l"(oxp + j * 64 + br) : "memory");
    };
    auto await_o = [&](uint4 (&u)[4], int br) {
        int it = 0;
        while (true) {
            uint32_t bad = 0;
#pragma unroll
            for (int j = 0; j < 4; j++) {
                u[j].x ^= tag; u[j].y ^= tag; u[j].z ^= tag; u[j].w ^= tag;
                bad |= (u[j].x | u[j].y) | (u[j].z | u[j].w);
            }
            if (__all_sync(~0u, !(bad & 0x10000u))) break;
            if (++it > (1 << 20)) __trap();
            fetch_o(u, br);
        }
    };
    uint4 ov[4];
    {
        const int grp = warp >> 2, seg = warp & 3;
        const uint32_t voff = sb + lrow * 512 + seg * 128 + lchunk;
        int slot = (T_V + grp) % NS;
        uint32_t ph = ((T_V + grp) / NS) & 1;
        uint32_t pa = sb + SM_P + (grp * 32 + g) * 4;
        auto pv = [&](int n) {
#pragma unroll 1
            for (int i = 0; i < n; i++) {
                const uint32_t wa = lds32(pa), wb = lds32(pa + 32), wc = lds32(pa + 64), wd = lds32(pa + 96);
                pa += 256;
                mbar_wait(bars + (B_FULL + slot) * 8, ph);
                gemv16(acc, voff + slot * TILE, __byte_perm(wa, 0, sel0), __byte_perm(wa, 0, sel1), __byte_perm(wb, 0, sel0), __byte_perm(wb, 0, sel1));
                gemv16(acc, voff + slot * TILE + 16 * 512, __byte_perm(wc, 0, sel0), __byte_perm(wc, 0, sel1), __byte_perm(wd, 0, sel0), __byte_perm(wd, 0, sel1));
                __syncwarp();
                if (lane == 0) mbar_arrive(bars + (B_EMPTY + slot) * 8, 2);
                slot += 2;
                if (slot >= NS) { slot -= NS; ph ^= 1; }
            }
        };
        auto send = [&](int br) {
            class_reduce<4>(acc);
            const uint32_t dst = sb + SM_OP + ((br * 16 + r * 2 + grp) * OSTR + (lane >> 3) * 16 + (lane & 3) * 4 + ((lane >> 2) & 1) * 2) * 4;
            st_async2(mapa(dst, seg), acc[0][0], acc[0][1], mapa(bars + (B_O + br) * 8, seg));
            st_async2(mapa(dst, 4 + seg), acc[0][2], acc[0][3], mapa(bars + (B_O + br) * 8, 4 + seg));
        };
        zero_acc(acc);
        pv(4);
        send(0);
        zero_acc(acc);
        pv(6);
        {
            mbar_wait_cluster(bars + B_STAT * 8, 0);
            const float2 ml = ldsf2(sb + SM_STAT + (lane & 15) * 8);
            float M = ml.x;
#pragma unroll
            for (int o = 4; o; o >>= 1) M = fmaxf(M, __shfl_xor_sync(~0u, M, o));
            const float e = exp2f(ml.x - M);
            float L = e * ml.y;
#pragma unroll
            for (int o = 4; o; o >>= 1) L += __shfl_xor_sync(~0u, L, o);
            const float gate = ldsf(sb + SM_MISC);
            wgt = ((lane & 8) ? bf_round(1.f - gate) : gate) * e / L;
            combine(0);
        }
        pv(6);
        if (h < 7) fetch_o(ov, 0);
        pv(4);
        if (tid == 128) TRACE_DEP(13, acc[7][0]);
        send(1);
        if (tid == 128) TRACE(8);
        combine(1);
        if (tid == 128) TRACE(10);
    }

    if (h < 7) {
        float c[4][4];
#pragma unroll
        for (int i = 0; i < 4; i++) { c[i][0] = c[i][1] = c[i][2] = c[i][3] = 0.f; }
        const uint32_t aoff = sb + (warp * 16 + (lane & 7) + (lane >> 4) * 8) * 128 + ((((lane >> 3) & 1) ^ (lane & 7)) << 4);
        const uint32_t bsel = (g & 1) ? 0x7632u : 0x5410u;
        auto oproj = [&](int br) {
            uint32_t b[4][2];
#pragma unroll
            for (int j = 0; j < 4; j++) { b[j][0] = __byte_perm(ov[j].x, ov[j].y, bsel); b[j][1] = __byte_perm(ov[j].z, ov[j].w, bsel); }
            uint32_t ok = mbar_test(bars + (B_WO + br * 4) * 8, 0);
#pragma unroll
            for (int j = 0; j < 4; j++) {
                if (br == 0 && j == 3) fetch_o(ov, 1);
                if (!ok) mbar_wait(bars + (B_WO + br * 4 + j) * 8, 0);
                if (tid == 128) TRACE(16 + br * 4 + j);
                if (j < 3) ok = mbar_test(bars + (B_WO + br * 4 + j + 1) * 8, 0);
                const uint32_t base = ((T_O + br * 4 + j) % NS) * TILE;
                uint32_t a[4][4];
#pragma unroll
                for (int i = 0; i < 4; i++)
                    asm volatile("ldmatrix.sync.aligned.m8n8.x4.trans.shared.b16 {%0,%1,%2,%3}, [%4];"
                                 : "=r"(a[i][0]), "=r"(a[i][1]), "=r"(a[i][2]), "=r"(a[i][3]) : "r"((aoff ^ (i << 5)) + base) : "memory");
#pragma unroll
                for (int i = 0; i < 4; i++) mma16816(c[i], a[i][0], a[i][1], a[i][2], a[i][3], b[j][0], b[j][1]);
            }
        };
        const uint32_t fdst = sb + SM_FIN + ((r * 8 + warp) * 8 + g) * 4;
        const uint32_t fd0 = mapa(fdst, 2 * t), fb0 = mapa(bars + B_FIN * 8, 2 * t);
        const uint32_t fd1 = mapa(fdst, 2 * t + 1), fb1 = mapa(bars + B_FIN * 8, 2 * t + 1);
        await_o(ov, 0);
        oproj(0);
        if (tid == 128) TRACE(9);
        await_o(ov, 1);
        if (tid == 128) TRACE(15);
        oproj(1);
        float u[4][2];
#pragma unroll
        for (int i = 0; i < 4; i++) { u[i][0] = c[i][0] + c[i][1]; u[i][1] = c[i][2] + c[i][3]; }
        const bool t1 = t & 1, t2 = t & 2;
        st_async1(fd0, __float_as_uint(sel(t2, sel(t1, u[3][0], u[2][0]), sel(t1, u[1][0], u[0][0]))), fb0);
        st_async1(fd1, __float_as_uint(sel(t2, sel(t1, u[3][1], u[2][1]), sel(t1, u[1][1], u[0][1]))), fb1);
        if (tid == 128) TRACE(12);
    }
    TRACE_DUMP();
}

typedef CUresult (*EncodeFn)(CUtensorMap*, CUtensorMapDataType, cuuint32_t, void*, const cuuint64_t*, const cuuint64_t*,
                             const cuuint32_t*, const cuuint32_t*, CUtensorMapInterleave, CUtensorMapSwizzle,
                             CUtensorMapL2promotion, CUtensorMapFloatOOBfill);

}

extern "C" void kernel_launch(void* const* d_in, const int* in_sizes, int n_in, void* d_out, int out_size) {
    (void)in_sizes; (void)n_in; (void)out_size;
    static EncodeFn encode = nullptr;
    static void *ox = nullptr, *epoch = nullptr;
    if (!encode) {
        cudaGetSymbolAddress(&ox, g_ox);
        cudaGetSymbolAddress(&epoch, g_epoch);
        cudaDriverEntryPointQueryResult qr;
        cudaGetDriverEntryPoint("cuTensorMapEncodeTiled", (void**)&encode, cudaEnableDefault, &qr);
        cudaFuncSetAttribute(fused_decode_kernel, cudaFuncAttributeMaxDynamicSharedMemorySize, SM_TOTAL + SM_EXTRA);
    }
    CUtensorMap tm[2], to[2];
    for (int b = 0; b < 2; b++) {
        const cuuint32_t es[2] = {1, 1};
        const cuuint64_t qdims[2] = {4096, D_MODEL}, qstr[1] = {8192};
        const cuuint32_t qbox[2] = {128, 64};
        encode(&tm[b], CU_TENSOR_MAP_DATA_TYPE_BFLOAT16, 2, d_in[b ? 8 : 3], qdims, qstr, qbox, es,
               CU_TENSOR_MAP_INTERLEAVE_NONE, CU_TENSOR_MAP_SWIZZLE_NONE, CU_TENSOR_MAP_L2_PROMOTION_NONE,
               CU_TENSOR_MAP_FLOAT_OOB_FILL_NONE);
        const cuuint64_t odims[2] = {D_MODEL, 4096}, ostr[1] = {896};
        const cuuint32_t obox[2] = {64, 128};
        encode(&to[b], CU_TENSOR_MAP_DATA_TYPE_BFLOAT16, 2, d_in[b ? 9 : 4], odims, ostr, obox, es,
               CU_TENSOR_MAP_INTERLEAVE_NONE, CU_TENSOR_MAP_SWIZZLE_128B, CU_TENSOR_MAP_L2_PROMOTION_NONE,
               CU_TENSOR_MAP_FLOAT_OOB_FILL_NONE);
    }
    Params p;
    p.x = (const char*)d_in[0]; p.gw = (const char*)d_in[10];
    p.k[0] = (const char*)d_in[1]; p.v[0] = (const char*)d_in[2];
    p.k[1] = (const char*)d_in[6]; p.v[1] = (const char*)d_in[7];
    p.out = (__nv_bfloat16*)d_out;
    p.ox = (uint32_t*)ox; p.epoch = (uint32_t*)epoch;
    fused_decode_kernel<<<NCTA, NTHR, SM_TOTAL + SM_EXTRA, cudaStreamPerThread>>>(p, tm[0], tm[1], to[0], to[1]);
}
```

```cpp
#include <cuda_runtime.h>
#include <cuda_bf16.h>
#include <cuda.h>
#include <stdint.h>

namespace {

constexpr int D_MODEL = 448;
constexpr int SK      = 8192;
constexpr int WIN     = 2048;
constexpr int NCTA    = 64;
constexpr int CL      = 8;
constexpr int NTHR    = 288;
constexpr int NS      = 12;
constexpr int TAU     = 326;
constexpr int OFFS    = 1360;
constexpr int GAP     = 300;
constexpr int TAUO    = 270;
constexpr int GDELAY  = 235;
constexpr int OWAIT   = 6;
constexpr int TILE    = 16384;
constexpr int T_K = 7, T_KB = 15, T_V = 47, T_O = 87;
constexpr int NINIT = T_K + 1;
constexpr float SC = 0.0625f * 1.4426950408889634f;
constexpr int OSTR = 72;
static_assert(NS >= 8 && NS % 2 == 0, "ring size");

constexpr int SM_RING  = 0;
constexpr int SM_Q     = SM_RING + NS * TILE;
constexpr int SM_X     = SM_Q + 2048;
constexpr int SM_GW    = SM_X + 896;
constexpr int SM_QRED  = SM_GW + 896;
constexpr int SM_S     = SM_QRED + 2048;
constexpr int SM_P     = SM_S + 10240;
constexpr int SM_OP    = SM_P + 5120;
constexpr int SM_STAT  = SM_OP + 2 * 16 * OSTR * 4;
constexpr int SM_RED   = SM_STAT + 128;
constexpr int SM_MISC  = SM_RED + 256;
constexpr int SM_BAR   = SM_MISC + 16;
constexpr int SM_FIN   = SM_QRED;
constexpr int SM_OV    = SM_S;
constexpr int B_FULL = 0, B_EMPTY = NS, B_X = 2 * NS, B_Q = B_X + 1, B_STAT = B_X + 2, B_O = B_X + 3;
constexpr int B_FIN = B_O + 2, B_OV = B_FIN + 1;
constexpr int B_WO = B_OV + 1;
constexpr int B_VL = B_WO + 64;
constexpr int NBAR     = B_VL + 8;
constexpr int SM_TOTAL = SM_BAR + NBAR * 8;

struct Params {
    const char* wq;
    const char* x; const char* gw;
    const char* k[2];
    uint32_t first, tau, gap, tauo;
    __nv_bfloat16* out;
    uint32_t* ox; uint32_t* epoch;
};
struct Maps { CUtensorMap wq[2], v[2], wo[2]; };

__device__ __align__(128) uint32_t g_ox[2 * 8 * 512];
__device__ uint32_t g_epoch[NCTA * 8];

__device__ __forceinline__ void mbar_init(uint32_t a, uint32_t c) {
    asm volatile("mbarrier.init.shared::cta.b64 [%0], %1;" ::"r"(a), "r"(c) : "memory");
}
__device__ __forceinline__ void mbar_expect(uint32_t a, uint32_t bytes) {
    asm volatile("mbarrier.arrive.expect_tx.shared::cta.b64 _, [%0], %1;" ::"r"(a), "r"(bytes) : "memory");
}
__device__ __forceinline__ void mbar_arrive(uint32_t a, uint32_t cnt) {
    asm volatile("mbarrier.arrive.shared::cta.b64 _, [%0], %1;" ::"r"(a), "r"(cnt) : "memory");
}
__device__ __forceinline__ void mbar_wait(uint32_t a, uint32_t parity) {
    asm volatile("{\n"
                 ".reg .pred p;\n"
                 ".reg .u32 n;\n"
                 "mov.u32 n, 0;\n"
                 "W_LOOP:\n"
                 "mbarrier.try_wait.parity.shared::cta.b64 p, [%0], %1;\n"
                 "@p bra W_DONE;\n"
                 "add.u32 n, n, 1;\n"
                 "setp.lt.u32 p, n, 0x100000;\n"
                 "@p bra W_LOOP;\n"
                 "trap;\n"
                 "W_DONE:\n"
                 "}" ::"r"(a), "r"(parity) : "memory");
}
__device__ __forceinline__ void mbar_wait_long(uint32_t a, uint32_t parity) {
    asm volatile("{\n"
                 ".reg .pred p, q;\n"
                 ".reg .u32 n;\n"
                 "mov.u32 n, 0;\n"
                 "W_LOOP:\n"
                 "setp.ge.u32 q, n, 0x100000;\n"
                 "@q trap;\n"
                 "add.u32 n, n, 1;\n"
                 "mbarrier.try_wait.parity.shared::cta.b64 p, [%0], %1;\n"
                 "@!p bra W_LOOP;\n"
                 "}" ::"r"(a), "r"(parity) : "memory");
}
__device__ __forceinline__ uint32_t mbar_test(uint32_t a, uint32_t parity) {
    uint32_t ok;
    asm volatile("{.reg .pred p; mbarrier.test_wait.parity.shared::cta.b64 p, [%1], %2; selp.u32 %0, 1, 0, p;}"
                 : "=r"(ok) : "r"(a), "r"(parity) : "memory");
    return ok;
}
__device__ __forceinline__ uint64_t stream_policy() {
    uint64_t pol;
    asm("createpolicy.fractional.L2::evict_first.b64 %0, 1.0;" : "=l"(pol));
    return pol;
}
__device__ __forceinline__ void mbar_init_fence() { asm volatile("fence.mbarrier_init.release.cluster;" ::: "memory"); }
__device__ __forceinline__ void bulk_load(uint32_t dst, const void* src, uint32_t bytes, uint32_t bar, uint64_t pol) {
    asm volatile("cp.async.bulk.shared::cluster.global.mbarrier::complete_tx::bytes.L2::cache_hint [%0], [%1], %2, [%3], %4;"
                 ::"r"(dst), "l"(src), "r"(bytes), "r"(bar), "l"(pol) : "memory");
}
__device__ __forceinline__ void tensor_load(uint32_t dst, const CUtensorMap* tm, int c0, int c1, uint32_t bar, uint64_t pol) {
    asm volatile("cp.async.bulk.tensor.2d.shared::cluster.global.mbarrier::complete_tx::bytes.L2::cache_hint [%0], [%1, {%3, %4}], [%2], %5;"
                 ::"r"(dst), "l"(tm), "r"(bar), "r"(c0), "r"(c1), "l"(pol) : "memory");
}
__device__ __forceinline__ uint32_t mapa(uint32_t a, uint32_t rank) {
    uint32_t r;
    asm("mapa.shared::cluster.u32 %0, %1, %2;" : "=r"(r) : "r"(a), "r"(rank));
    return r;
}
__device__ __forceinline__ void st_async2(uint32_t a, float x, float y, uint32_t bar) {
    asm volatile("st.async.shared::cluster.mbarrier::complete_tx::bytes.v2.f32 [%0], {%1, %2}, [%3];"
                 ::"r"(a), "f"(x), "f"(y), "r"(bar) : "memory");
}
__device__ __forceinline__ bool elect_one() {
    uint32_t p;
    asm volatile("{.reg .pred P; elect.sync _|P, 0xffffffff; selp.u32 %0, 1, 0, P;}" : "=r"(p));
    return p;
}
__device__ __forceinline__ void cons_sync() { asm volatile("bar.sync 1, 256;" ::: "memory"); }

__device__ __forceinline__ uint32_t lds32(uint32_t a) {
    uint32_t v; asm volatile("ld.shared.u32 %0, [%1];" : "=r"(v) : "r"(a) : "memory"); return v;
}
__device__ __forceinline__ float ldsf(uint32_t a) {
    float v; asm volatile("ld.shared.f32 %0, [%1];" : "=f"(v) : "r"(a) : "memory"); return v;
}
__device__ __forceinline__ float2 ldsf2(uint32_t a) {
    float2 v; asm volatile("ld.shared.v2.f32 {%0, %1}, [%2];" : "=f"(v.x), "=f"(v.y) : "r"(a) : "memory"); return v;
}
__device__ __forceinline__ float4 ldsf4(uint32_t a) {
    float4 v; asm volatile("ld.shared.v4.f32 {%0, %1, %2, %3}, [%4];" : "=f"(v.x), "=f"(v.y), "=f"(v.z), "=f"(v.w) : "r"(a) : "memory"); return v;
}
__device__ __forceinline__ uint4 lds128(uint32_t a) {
    uint4 v; asm volatile("ld.shared.v4.u32 {%0, %1, %2, %3}, [%4];" : "=r"(v.x), "=r"(v.y), "=r"(v.z), "=r"(v.w) : "r"(a) : "memory"); return v;
}
__device__ __forceinline__ void sts32(uint32_t a, uint32_t v) { asm volatile("st.shared.u32 [%0], %1;" ::"r"(a), "r"(v) : "memory"); }
__device__ __forceinline__ void sts16(uint32_t a, uint32_t v) { asm volatile("st.shared.u16 [%0], %1;" ::"r"(a), "h"((uint16_t)v) : "memory"); }
__device__ __forceinline__ void stsf2(uint32_t a, float x, float y) { asm volatile("st.shared.v2.f32 [%0], {%1, %2};" ::"r"(a), "f"(x), "f"(y) : "memory"); }
__device__ __forceinline__ void stsf4(uint32_t a, float x, float y, float z, float w) {
    asm volatile("st.shared.v4.f32 [%0], {%1, %2, %3, %4};" ::"r"(a), "f"(x), "f"(y), "f"(z), "f"(w) : "memory");
}
__device__ __forceinline__ uint32_t pack_bf16(float lo, float hi) {
    uint32_t r; asm("cvt.rn.bf16x2.f32 %0, %1, %2;" : "=r"(r) : "f"(hi), "f"(lo)); return r;
}
__device__ __forceinline__ float sel(int p, float a, float b) {
    float r; asm("{.reg .pred q; setp.ne.u32 q, %3, 0; selp.f32 %0, %1, %2, q;}" : "=f"(r) : "f"(a), "f"(b), "r"((uint32_t)p)); return r;
}
__device__ __forceinline__ float ex2(float x) { float r; asm("ex2.approx.ftz.f32 %0, %1;" : "=f"(r) : "f"(x)); return r; }
__device__ __forceinline__ float bf_lo(uint32_t v) { return __uint_as_float(v << 16); }
__device__ __forceinline__ float bf_hi(uint32_t v) { return __uint_as_float(v & 0xffff0000u); }
__device__ __forceinline__ float bf_round(float x) { return __bfloat162float(__float2bfloat16_rn(x)); }

__device__ __forceinline__ void mma16816(float (&c)[4], uint32_t a0, uint32_t a1, uint32_t a2, uint32_t a3, uint32_t b0, uint32_t b1) {
    asm volatile("mma.sync.aligned.m16n8k16.row.col.f32.bf16.bf16.f32 {%0,%1,%2,%3}, {%4,%5,%6,%7}, {%8,%9}, {%0,%1,%2,%3};"
                 : "+f"(c[0]), "+f"(c[1]), "+f"(c[2]), "+f"(c[3])
                 : "r"(a0), "r"(a1), "r"(a2), "r"(a3), "r"(b0), "r"(b1));
}

__device__ __forceinline__ void load_a(uint32_t (&a)[4][4], uint32_t addr, uint32_t off) {
#pragma unroll
    for (int i = 0; i < 4; i++)
        asm volatile("ldmatrix.sync.aligned.m8n8.x4.trans.shared.b16 {%0,%1,%2,%3}, [%4];"
                     : "=r"(a[i][0]), "=r"(a[i][1]), "=r"(a[i][2]), "=r"(a[i][3]) : "r"((addr ^ (i << 5)) + off) : "memory");
}
__device__ __forceinline__ void mma_a(float (&c)[4][4], const uint32_t (&a)[4][4], uint32_t b0, uint32_t b1) {
#pragma unroll
    for (int i = 0; i < 4; i++) mma16816(c[i], a[i][0], a[i][1], a[i][2], a[i][3], b0, b1);
}
__device__ __forceinline__ void zero_acc(float (&c)[4][4]) {
#pragma unroll
    for (int i = 0; i < 4; i++) { c[i][0] = c[i][1] = c[i][2] = c[i][3] = 0.f; }
}
__device__ __forceinline__ float pick(int t, float v0, float v1, float v2, float v3) {
    return sel(t & 2, sel(t & 1, v3, v2), sel(t & 1, v1, v0));
}

__device__ __forceinline__ float pick_sum(int t, const float (&c)[4][4], int j) {
    float r;
    asm("{.reg .pred p1, p2, p3; setp.eq.u32 p1, %9, 1; setp.eq.u32 p2, %9, 2; setp.eq.u32 p3, %9, 3;\n"
        "add.f32 %0, %1, %2; @p1 add.f32 %0, %3, %4; @p2 add.f32 %0, %5, %6; @p3 add.f32 %0, %7, %8;}"
        : "=&f"(r) : "f"(c[0][j]), "f"(c[0][j + 1]), "f"(c[1][j]), "f"(c[1][j + 1]), "f"(c[2][j]), "f"(c[2][j + 1]),
          "f"(c[3][j]), "f"(c[3][j + 1]), "r"(t));
    return r;
}

__device__ __forceinline__ void fetch_o(uint4 (&u)[4], const uint4* src) {
#pragma unroll
    for (int j = 0; j < 4; j++)
        asm volatile("ld.relaxed.gpu.global.v4.u32 {%0,%1,%2,%3}, [%4];"
                     : "=r"(u[j].x), "=r"(u[j].y), "=r"(u[j].z), "=r"(u[j].w) : "l"(src + j * 32) : "memory");
}
__device__ __forceinline__ bool check_o(uint4 (&u)[4], uint32_t tag) {
    uint32_t bad = 0;
#pragma unroll
    for (int j = 0; j < 4; j++) {
        u[j].x ^= tag; u[j].y ^= tag; u[j].z ^= tag; u[j].w ^= tag;
        bad |= (u[j].x | u[j].y) | (u[j].z | u[j].w);
    }
    return __all_sync(~0u, !(bad & 0x10000u));
}

__global__ void __cluster_dims__(CL, 1, 1) __launch_bounds__(NTHR, 1)
fused_decode_kernel(const __grid_constant__ Params P, const __grid_constant__ Maps M)
{
    extern __shared__ __align__(1024) char smem_raw[];
    uint32_t sb;
    int tid, cta;
    asm volatile("mov.u32 %0, %%ctaid.x;" : "=r"(cta));
    asm volatile("mov.u32 %0, %%tid.x;" : "=r"(tid));
    asm volatile("prefetch.global.L2 [%0];" ::"l"(P.wq + (size_t)((uint32_t)cta * NTHR + (uint32_t)tid) * 128) : "memory");
    if (cta >= NCTA) return;
    asm volatile("mov.u32 %0, %1;" : "=r"(sb) : "r"((uint32_t)__cvta_generic_to_shared(smem_raw)));
    const int warp = __shfl_sync(~0u, tid >> 5, 0), lane = tid & 31;
    const int h = cta >> 3, r = cta & 7;
    const uint32_t bars = sb + SM_BAR;
    const size_t kvoffB = (size_t)h * (SK * 512) + r * TILE, kvoffA = kvoffB + (SK - WIN) * 512;

    uint32_t t0 = 0, epoch_ld = 0;
    if (warp == 0) {
        if (elect_one()) {
            const uint64_t pol = stream_policy();
            const CUtensorMap* tm = &M.wq[r >> 2];
            asm volatile("prefetch.tensormap [%0];" ::"l"(tm) : "memory");
#pragma unroll
            for (int i = 0; i < NINIT; i++) mbar_init(bars + (B_FULL + i) * 8, 1);
            mbar_init_fence();
#pragma unroll 1
            for (int i = 0; i < T_K; i++) {
                mbar_expect(bars + (B_FULL + i) * 8, TILE);
                tensor_load(sb + i * TILE, tm, h * 512 + (r & 3) * 128, i * 64, bars + (B_FULL + i) * 8, pol);
                tensor_load(sb + i * TILE + 8192, tm, h * 512 + (r & 3) * 128 + 64, i * 64, bars + (B_FULL + i) * 8, pol);
            }
            mbar_expect(bars + (B_FULL + T_K) * 8, TILE);
            bulk_load(sb + T_K * TILE, P.k[0] + kvoffA, TILE, bars + (B_FULL + T_K) * 8, pol);
        }
    }
    asm volatile("" ::: "memory");
    if (warp == 1) {
        if (elect_one()) {
            const uint64_t pol = stream_policy();
            mbar_init(bars + B_X * 8, 1);
            mbar_init_fence();
            mbar_expect(bars + B_X * 8, 2 * 896);
            bulk_load(sb + SM_X, P.x, 896, bars + B_X * 8, pol);
            bulk_load(sb + SM_GW, P.gw, 896, bars + B_X * 8, pol);
        }
    }
    asm volatile("" ::: "memory");
    if (warp == 2) {
        if (elect_one()) {
#pragma unroll
            for (int i = 0; i < NS; i++) mbar_init(bars + (B_EMPTY + i) * 8, 8);
#pragma unroll
            for (int i = NINIT; i < NS; i++) mbar_init(bars + (B_FULL + i) * 8, 1);
#pragma unroll
            for (int i = B_Q; i <= B_OV; i++) mbar_init(bars + i * 8, 1);
            mbar_expect(bars + B_Q * 8, 2048);
            mbar_expect(bars + B_STAT * 8, 128);
            mbar_expect(bars + B_O * 8, 4096);
            mbar_expect(bars + (B_O + 1) * 8, 4096);
            mbar_expect(bars + B_FIN * 8, 2048);
            mbar_init_fence();
        }
    }
    if (tid == 128) asm volatile("ld.relaxed.gpu.global.u32 %0, [%1];" : "=r"(epoch_ld) : "l"(P.epoch + cta * 8) : "memory");
    if (warp == 8) asm volatile("mov.u32 %0, %%globaltimer_lo;" : "=r"(t0));
    __syncthreads();
    asm volatile("barrier.cluster.arrive.relaxed.aligned;" ::: "memory");

    if (warp == 8) {
        asm volatile("barrier.cluster.wait.aligned;" ::: "memory");
        if (elect_one()) {
            const uint64_t pol = stream_policy();
            uint32_t due = t0 + P.first;
            const uint32_t tau = P.tau;
            auto pace = [&](uint32_t dt) {
                uint32_t now;
                int it = 0;
                do { asm volatile("mov.u32 %0, %%globaltimer_lo;" : "=r"(now)); } while ((int)(now - due) < 0 && ++it < 256);
                due += dt;
            };
            int slot = NINIT % NS;
            uint32_t ph = NINIT < NS;
            auto acquire = [&](uint32_t dt) { mbar_wait(bars + (B_EMPTY + slot) * 8, ph); pace(dt); };
            auto advance = [&]() { if (++slot == NS) { slot = 0; ph ^= 1; } };
#pragma unroll
            for (int i = 0; i < 2; i++) {
                asm volatile("prefetch.tensormap [%0];" ::"l"(&M.v[i]) : "memory");
                asm volatile("prefetch.tensormap [%0];" ::"l"(&M.wo[i]) : "memory");
            }
            const char* src = P.k[0] + kvoffA + (NINIT - T_K) * (CL * TILE);
#pragma unroll 1
            for (int T = NINIT; T < T_V; T++) {
                if (T == T_KB) src = P.k[1] + kvoffB;
                acquire(tau);
                mbar_expect(bars + (B_FULL + slot) * 8, TILE);
                bulk_load(sb + slot * TILE, src, TILE, bars + (B_FULL + slot) * 8, pol);
                src += CL * TILE;
                advance();
            }
            int row = h * SK + (SK - WIN) + r * 32;
#pragma unroll 1
            for (int i = 0; i < 40; i++) {
                if (i == 8) row = h * SK + r * 32;
                acquire(tau);
                const uint32_t bar = bars + (i < 38 ? B_FULL + slot : B_VL + (i - 38) * 4) * 8, step = i < 38 ? 0 : 8;
                if (i < 38) mbar_expect(bar, TILE);
#pragma unroll
                for (int s = 0; s < 4; s++) tensor_load(sb + slot * TILE + s * 4096, &M.v[i >= 8], s * 64, row, bar + s * step, pol);
                row += CL * 32;
                advance();
            }
            if (h < 7) {
                due += P.gap;
                const uint32_t tauo = P.tauo;
#pragma unroll 1
                for (int i = 0; i < 8; i++) {
                    acquire(i < 7 ? tauo : GDELAY);
#pragma unroll
                    for (int w = 0; w < 8; w++)
                        tensor_load(sb + slot * TILE + w * 2048, &M.wo[i >> 2], h * 64, r * 512 + (i & 3) * 128 + w * 16,
                                    bars + (B_WO + i * 8 + w) * 8, pol);
                    advance();
                }
                pace(0);
            }
        }
        __syncwarp();
        if (h < 7) {
            {
                const uint32_t tag = ((lds32(sb + SM_MISC + 4) & 1) ^ 1) << 16;
                const uint4* src = reinterpret_cast<const uint4*>(P.ox) + (1024 + r * 128 + lane);
                uint4 u[4];
                int it = 0;
                do {
                    fetch_o(u, src);
                    if (++it > (1 << 20)) __trap();
                } while (!check_o(u, tag));
#pragma unroll
                for (int j = 0; j < 4; j++)
                    asm volatile("st.shared.v4.u32 [%0], {%1, %2, %3, %4};" ::"r"(sb + SM_OV + (j * 32 + lane) * 16),
                                 "r"(__byte_perm(u[j].x, u[j].y, 0x5410)), "r"(__byte_perm(u[j].z, u[j].w, 0x5410)),
                                 "r"(__byte_perm(u[j].x, u[j].y, 0x7632)), "r"(__byte_perm(u[j].z, u[j].w, 0x7632)) : "memory");
                __syncwarp();
                if (lane == 0) mbar_arrive(bars + B_OV * 8, 1);
            }
            __nv_bfloat16* outp = P.out + (h * 64 + (r >> 1) * 16 + (r & 1) * 4 + ((lane & 7) >> 1) + (lane & 1) * 8);
            uint32_t fa = sb + SM_FIN + lane * 16;
            asm volatile("" : "+l"(outp), "+r"(fa));
            mbar_wait_long(bars + B_FIN * 8, 0);
            float v[16];
#pragma unroll
            for (int i = 0; i < 4; i++)
                asm volatile("ldmatrix.sync.aligned.m8n8.x4.shared.b16 {%0,%1,%2,%3}, [%4];"
                             : "=f"(v[4 * i]), "=f"(v[4 * i + 1]), "=f"(v[4 * i + 2]), "=f"(v[4 * i + 3]) : "r"(fa + i * 512) : "memory");
            float w = ((v[0] + v[1]) + (v[2] + v[3])) + ((v[4] + v[5]) + (v[6] + v[7]));
            w = (w + ((v[8] + v[9]) + (v[10] + v[11]))) + ((v[12] + v[13]) + (v[14] + v[15]));
            const float w1 = __shfl_xor_sync(~0u, w, 8), w2 = __shfl_xor_sync(~0u, w, 16), w3 = __shfl_xor_sync(~0u, w, 24);
            w = (w + w1) + (w2 + w3);
            asm volatile("st.global.u16 [%0], %1;" ::"l"(outp), "h"(__bfloat16_as_ushort(__float2bfloat16_rn(w))) : "memory");
        }
        return;
    }

    const int g = lane >> 2, t = lane & 3;
    const uint32_t lda = sb + ((lane & 7) + (lane >> 4) * 8) * 128 + ((((lane >> 3) & 1) ^ (lane & 7)) << 4);
    float c[4][4];
    uint32_t a[4][4][4];

    if (elect_one()) {
        const uint32_t wb = bars + (B_WO + warp) * 8;
#pragma unroll
        for (int i = 0; i < 9; i++) mbar_init(wb + i * 64, 1);
        mbar_init_fence();
#pragma unroll
        for (int i = 0; i < 9; i++) mbar_expect(wb + i * 64, i < 8 ? TILE / 8 : TILE / 4);
    }
    __syncwarp();

    mbar_wait(bars + B_X * 8, 0);
    if (warp == 7) {
        float s = 0.f;
#pragma unroll 1
        for (int i = 0; i < 7; i++) {
            const uint32_t xv = lds32(sb + SM_X + (i * 32 + lane) * 4), gv = lds32(sb + SM_GW + (i * 32 + lane) * 4);
            s += bf_round(bf_lo(xv) * bf_lo(gv)) + bf_round(bf_hi(xv) * bf_hi(gv));
        }
#pragma unroll
        for (int o = 16; o; o >>= 1) s += __shfl_xor_sync(~0u, s, o);
        s = bf_round(s);
        if (lane == 0) sts32(sb + SM_MISC, __float_as_uint(bf_round(__fdividef(1.f, 1.f + __expf(-s)))));
    }
    {
        const int seg = warp & 1, ks = warp >> 1;
        const uint32_t qa = lda + seg * 8192 + ks * 2048, xa = sb + SM_X + ks * 32 + t * 4;
        zero_acc(c);
#pragma unroll 1
        for (int T = 0; T < T_K; T++) {
            const uint32_t b0 = lds32(xa + T * 128), b1 = lds32(xa + T * 128 + 16);
            mbar_wait(bars + (B_FULL + T) * 8, 0);
            load_a(a[0], qa + T * TILE, 0);
            mma_a(c, a[0], b0, b1);
            __syncwarp();
            if (lane == 0) mbar_arrive(bars + (B_EMPTY + T) * 8, 1);
        }
        if (tid == 128) { sts32(sb + SM_MISC + 4, epoch_ld); P.epoch[cta * 8] = epoch_ld + 1; }
        const uint32_t qr = sb + SM_QRED + (ks * 128 + seg * 64 + t * 16 + g) * 4;
        sts32(qr, __float_as_uint(pick(t, c[0][0], c[1][0], c[2][0], c[3][0])));
        sts32(qr + 32, __float_as_uint(pick(t, c[0][2], c[1][2], c[2][2], c[3][2])));
        asm volatile("barrier.cluster.wait.aligned;" ::: "memory");
        cons_sync();
        float4 q4 = ldsf4(sb + SM_QRED + lane * 16);
#pragma unroll
        for (int i = 1; i < 4; i++) {
            const float4 b = ldsf4(sb + SM_QRED + i * 512 + lane * 16);
            q4.x += b.x; q4.y += b.y; q4.z += b.z; q4.w += b.w;
        }
        st_async2(mapa(sb + SM_Q + r * 256 + lane * 8, warp), __uint_as_float(pack_bf16(q4.x, q4.y)), __uint_as_float(pack_bf16(q4.z, q4.w)),
                  mapa(bars + B_Q * 8, warp));
    }

    {
        mbar_wait(bars + B_Q * 8, 0);
        const uint32_t koff = ((warp & 1) * 16 + g) * 512 + (t + 4 * (g & 1)) * 16;
        const uint32_t qoff = sb + SM_Q + (g & 1) * 512 + (t + 4 * ((g >> 1) & 1)) * 16;
        const uint32_t soff = sb + SM_S + ((warp & 1) * 16 + g + 8 * (t >> 1)) * 8;
        const bool swr = (t & 1) == (g & 1);
        int slot = T_K % NS;
        uint32_t ph = (T_K / NS) & 1;
#pragma unroll 1
        for (int br = 0; br < 2; br++) {
            uint4 q[8];
#pragma unroll
            for (int s = 0; s < 8; s++) q[s] = lds128((qoff + br * 1024) ^ (s << 6));
            const int T0 = br ? T_KB : T_K, T1 = br ? T_V : T_KB;
#pragma unroll 1
            for (int T = T0; T < T1; T++) {
                if ((slot & 3) == (warp >> 1)) {
                    mbar_wait(bars + (B_FULL + slot) * 8, ph);
                    const uint32_t ad = sb + slot * TILE + koff;
                    zero_acc(c);
                    uint4 ka[8], kb[8];
#pragma unroll
                    for (int s = 0; s < 8; s++) { ka[s] = lds128(ad ^ (s << 6)); kb[s] = lds128((ad + 8 * 512) ^ (s << 6)); }
#pragma unroll
                    for (int s = 0; s < 8; s++) {
                        mma16816(c[(2 * s) & 3], ka[s].x, kb[s].x, ka[s].y, kb[s].y, q[s].x, q[s].y);
                        mma16816(c[(2 * s + 1) & 3], ka[s].z, kb[s].z, ka[s].w, kb[s].w, q[s].z, q[s].w);
                    }
                    __syncwarp();
                    if (lane == 0) mbar_arrive(bars + (B_EMPTY + slot) * 8, 4);
                    const float s0 = (c[0][0] + c[1][0]) + (c[2][0] + c[3][0]), s1 = (c[0][1] + c[1][1]) + (c[2][1] + c[3][1]);
                    const float s2 = (c[0][2] + c[1][2]) + (c[2][2] + c[3][2]), s3 = (c[0][3] + c[1][3]) + (c[2][3] + c[3][3]);
                    if (swr) stsf2(soff + (T - T_K) * 256, (t >> 1) ? s2 : s0, (t >> 1) ? s3 : s1);
                }
                if (++slot == NS) { slot = 0; ph ^= 1; }
            }
        }
    }

    {
        cons_sync();
        float2 s[5];
#pragma unroll
        for (int i = 0; i < 5; i++) { s[i] = ldsf2(sb + SM_S + (i * 256 + tid) * 8); s[i].x = bf_round(s[i].x); s[i].y = bf_round(s[i].y); }
        float m0 = s[0].x, m1 = s[0].y;
        float m2 = fmaxf(fmaxf(s[1].x, s[2].x), fmaxf(s[3].x, s[4].x)), m3 = fmaxf(fmaxf(s[1].y, s[2].y), fmaxf(s[3].y, s[4].y));
#pragma unroll
        for (int o = 16; o; o >>= 1) {
            m0 = fmaxf(m0, __shfl_xor_sync(~0u, m0, o)); m1 = fmaxf(m1, __shfl_xor_sync(~0u, m1, o));
            m2 = fmaxf(m2, __shfl_xor_sync(~0u, m2, o)); m3 = fmaxf(m3, __shfl_xor_sync(~0u, m3, o));
        }
        if (lane == 0) stsf4(sb + SM_RED + warp * 16, m0, m1, m2, m3);
        cons_sync();
#pragma unroll
        for (int w = 0; w < 8; w++) {
            const float4 v = ldsf4(sb + SM_RED + w * 16);
            m0 = fmaxf(m0, v.x); m1 = fmaxf(m1, v.y); m2 = fmaxf(m2, v.z); m3 = fmaxf(m3, v.w);
        }
        float l0, l1, l2 = 0.f, l3 = 0.f;
        l0 = ex2((s[0].x - m0) * SC); l1 = ex2((s[0].y - m1) * SC);
        const uint32_t pw = sb + SM_P + warp * 128 + ((lane & 7) >> 1) * 16 + (lane >> 3) * 4 + (lane & 1) * 2;
        const uint32_t p01 = pack_bf16(l0, l1);
        sts16(pw, p01); sts16(pw + 64, p01 >> 16);
#pragma unroll
        for (int i = 1; i < 5; i++) {
            const float e0 = ex2((s[i].x - m2) * SC), e1 = ex2((s[i].y - m3) * SC);
            l2 += e0; l3 += e1;
            const uint32_t p23 = pack_bf16(e0, e1);
            sts16(pw + i * 1024, p23); sts16(pw + i * 1024 + 64, p23 >> 16);
        }
#pragma unroll
        for (int o = 16; o; o >>= 1) {
            l0 += __shfl_xor_sync(~0u, l0, o); l1 += __shfl_xor_sync(~0u, l1, o);
            l2 += __shfl_xor_sync(~0u, l2, o); l3 += __shfl_xor_sync(~0u, l3, o);
        }
        if (lane == 0) stsf4(sb + SM_RED + 128 + warp * 16, l0, l1, l2, l3);
        cons_sync();
        if (warp == 0 && lane < 16) {
            const int dest = lane & 7, br = lane >> 3, j = br * 2 + (dest >> 2);
            float l = 0.f;
#pragma unroll
            for (int w = 0; w < 8; w++) l += ldsf(sb + SM_RED + 128 + w * 16 + j * 4);
            const float m = j == 0 ? m0 : j == 1 ? m1 : j == 2 ? m2 : m3;
            st_async2(mapa(sb + SM_STAT + (br * 8 + r) * 8, dest), m, l, mapa(bars + B_STAT * 8, dest));
        }
    }

    const uint32_t tag = ((lds32(sb + SM_MISC + 4) & 1) ^ 1) << 16;
    float wgt = 0.f;
    auto combine = [&](int br) {
        const int vi = tid >> 2, pos = (vi & ~3) | ((vi >> 1) & 1) | ((vi & 1) << 1);
        uint32_t* dst = P.ox + (br * 4096 + cta * 64 + pos);
        uint32_t src = sb + SM_OP + ((br * 16 + t) * OSTR + vi) * 4;
        float w4[4];
#pragma unroll
        for (int k = 0; k < 4; k++) w4[k] = __shfl_sync(~0u, wgt, br * 8 + ((t + 4 * k) >> 1));
        asm volatile("" : "+l"(dst), "+r"(src));
        mbar_wait(bars + (B_O + br) * 8, 0);
        float p4[4];
#pragma unroll
        for (int k = 0; k < 4; k++) p4[k] = ldsf(src + 4 * k * OSTR * 4);
        float o = (w4[0] * p4[0] + w4[1] * p4[1]) + (w4[2] * p4[2] + w4[3] * p4[3]);
        const float o1 = __shfl_xor_sync(~0u, o, 1), o2 = __shfl_xor_sync(~0u, o, 2), o3 = __shfl_xor_sync(~0u, o, 3);
        o = (o + o1) + (o2 + o3);
        const uint32_t hi = pack_bf16(o, 0.f);
        const uint32_t word = (pack_bf16(o, o - bf_lo(hi)) & ~0x10000u) | tag;
        if (t == 0) asm volatile("st.relaxed.gpu.global.u32 [%0], %1;" ::"l"(dst), "r"(word) : "memory");
    };
    uint32_t ob[4][2];
    {
        const int grp = warp >> 2, seg = warp & 3;
        const uint32_t va = lda + seg * 4096;
        int slot = (T_V + grp) % NS;
        uint32_t ph = ((T_V + grp) / NS) & 1;
        uint32_t pa = sb + SM_P + grp * 128 + (g & 1) * 64 + t * 16;
        const uint32_t odst = sb + SM_OP + ((r * 2 + grp) * OSTR + t * 16 + g * 2) * 4;
        uint32_t od0 = mapa(odst, seg), od1 = mapa(odst, 4 + seg), obar0 = mapa(bars + B_O * 8, seg), obar1 = mapa(bars + B_O * 8, 4 + seg);
        auto send = [&](int br) {
            st_async2(od0 + br * (16 * OSTR * 4), pick(t, c[0][0], c[1][0], c[2][0], c[3][0]), pick(t, c[0][2], c[1][2], c[2][2], c[3][2]), obar0 + br * 8);
            st_async2(od1 + br * (16 * OSTR * 4), pick(t, c[0][1], c[1][1], c[2][1], c[3][1]), pick(t, c[0][3], c[1][3], c[2][3], c[3][3]), obar1 + br * 8);
        };
        const uint4* oxp = reinterpret_cast<const uint4*>(P.ox) + (r * 128 + warp * 4 + t);
        uint4 u[4];
        zero_acc(c);
#pragma unroll 1
        for (int i = 0; i < 20; i++) {
            const uint4 p = lds128(pa);
            pa += 256;
            mbar_wait(bars + (i < 19 ? B_FULL + slot : B_VL + warp) * 8, i < 19 ? ph : 0);
            load_a(a[0], va + slot * TILE, 0);
            load_a(a[1], va + slot * TILE, 2048);
            mma_a(c, a[0], p.x, p.y);
            mma_a(c, a[1], p.z, p.w);
            __syncwarp();
            if (lane == 0) mbar_arrive(bars + (B_EMPTY + slot) * 8, 2);
            slot += 2;
            if (slot >= NS) { slot -= NS; ph ^= 1; }
            if (i == 3) {
                send(0);
                zero_acc(c);
            } else if (i == 9) {
                mbar_wait(bars + B_STAT * 8, 0);
                const float2 ml = ldsf2(sb + SM_STAT + (lane & 15) * 8);
                float Mx = ml.x;
#pragma unroll
                for (int o = 4; o; o >>= 1) Mx = fmaxf(Mx, __shfl_xor_sync(~0u, Mx, o));
                const float e = ex2((ml.x - Mx) * SC);
                float L = e * ml.y;
#pragma unroll
                for (int o = 4; o; o >>= 1) L += __shfl_xor_sync(~0u, L, o);
                const float gate = ldsf(sb + SM_MISC);
                wgt = ((lane & 8) ? bf_round(1.f - gate) : gate) * __fdividef(e, L);
                combine(0);
            } else if (i == 14) {
                if (h < 7) fetch_o(u, oxp);
            } else if (i == 16) {
                if (h < 7) {
                    int it = 0;
                    while (!check_o(u, tag)) {
                        if (++it > (1 << 20)) __trap();
                        fetch_o(u, oxp);
                    }
                    const uint32_t bsel = (g & 1) ? 0x7632u : 0x5410u;
#pragma unroll
                    for (int j = 0; j < 4; j++) { ob[j][0] = __byte_perm(u[j].x, u[j].y, bsel); ob[j][1] = __byte_perm(u[j].z, u[j].w, bsel); }
                }
            }
        }
        send(1);
        combine(1);
    }

    if (h < 7) {
        const uint32_t oa = lda + warp * 2048, wbar = bars + (B_WO + warp) * 8;
        const uint32_t fdst = mapa(sb + SM_FIN + ((r * 8 + warp) * 8 + (g & 3) * 2) * 4, 2 * t + (g >> 2));
        const uint32_t fbar = mapa(bars + B_FIN * 8, 2 * t + (g >> 2));
        uint32_t ova = sb + SM_OV + (warp * 4 + t) * 16 + (g & 1) * 8;
        asm volatile("" : "+r"(ova));
        zero_acc(c);
        uint32_t ok = mbar_test(wbar, 0);
#pragma unroll
        for (int j = 0; j < 8; j++) {
            if (j == OWAIT) {
                mbar_wait(bars + B_OV * 8, 0);
#pragma unroll
                for (int k = 0; k < 4; k++) {
                    const float2 v = ldsf2(ova + k * 512);
                    ob[k][0] = __float_as_uint(v.x); ob[k][1] = __float_as_uint(v.y);
                }
                ok = mbar_test(wbar + j * 64, 0);
#pragma unroll
                for (int k = 4; k < OWAIT; k++) mma_a(c, a[k & 3], ob[k & 3][0], ob[k & 3][1]);
            }
            if (!ok) mbar_wait_long(wbar + j * 64, 0);
            load_a(a[j & 3], oa, ((T_O + j) % NS) * TILE);
            if (j < 7 && j + 1 != OWAIT) ok = mbar_test(wbar + (j + 1) * 64, 0);
            if (j < 4 || j >= OWAIT) mma_a(c, a[j & 3], ob[j & 3][0], ob[j & 3][1]);
        }
        st_async2(fdst, pick_sum(t, c, 0), pick_sum(t, c, 2), fbar);
    }
}

typedef CUresult (*EncodeFn)(CUtensorMap*, CUtensorMapDataType, cuuint32_t, void*, const cuuint64_t*, const cuuint64_t*,
                             const cuuint32_t*, const cuuint32_t*, CUtensorMapInterleave, CUtensorMapSwizzle,
                             CUtensorMapL2promotion, CUtensorMapFloatOOBfill);

}

extern "C" void kernel_launch(void* const* d_in, const int* in_sizes, int n_in, void* d_out, int out_size) {
    (void)in_sizes; (void)n_in; (void)out_size;
    static EncodeFn encode = nullptr;
    static void *ox = nullptr, *epoch = nullptr;
    static double tscale = 1.0;
    if (!encode) {
        cudaGetSymbolAddress(&ox, g_ox);
        cudaGetSymbolAddress(&epoch, g_epoch);
        cudaDriverEntryPointQueryResult qr;
        cudaGetDriverEntryPoint("cuTensorMapEncodeTiled", (void**)&encode, cudaEnableDefault, &qr);
        cudaFuncSetAttribute(fused_decode_kernel, cudaFuncAttributeMaxDynamicSharedMemorySize, SM_TOTAL);
        int dev = 0, khz = 0, bits = 0;
        cudaGetDevice(&dev);
        if (cudaDeviceGetAttribute(&khz, cudaDevAttrMemoryClockRate, dev) == cudaSuccess &&
            cudaDeviceGetAttribute(&bits, cudaDevAttrGlobalMemoryBusWidth, dev) == cudaSuccess && khz > 0 && bits > 0)
            tscale = (2619000.0 * 5120.0) / ((double)khz * bits);
        if (!(tscale > 0.25 && tscale < 4.0)) tscale = 1.0;
    }
    Maps m;
    auto map2d = [&](CUtensorMap* tm, void* base, cuuint64_t cols, cuuint64_t rows, cuuint32_t box_rows) {
        const cuuint64_t dims[2] = {cols, rows}, strides[1] = {cols * 2};
        const cuuint32_t box[2] = {64, box_rows}, es[2] = {1, 1};
        encode(tm, CU_TENSOR_MAP_DATA_TYPE_BFLOAT16, 2, base, dims, strides, box, es, CU_TENSOR_MAP_INTERLEAVE_NONE,
               CU_TENSOR_MAP_SWIZZLE_128B, CU_TENSOR_MAP_L2_PROMOTION_NONE, CU_TENSOR_MAP_FLOAT_OOB_FILL_NONE);
    };
    for (int b = 0; b < 2; b++) {
        map2d(&m.wq[b], d_in[b ? 8 : 3], 4096, D_MODEL, 64);
        map2d(&m.v[b], d_in[b ? 7 : 2], 256, 8 * SK, 32);
        map2d(&m.wo[b], d_in[b ? 9 : 4], D_MODEL, 4096, 16);
    }
    Params p;
    p.wq = (const char*)d_in[3];
    p.x = (const char*)d_in[0]; p.gw = (const char*)d_in[10];
    p.k[0] = (const char*)d_in[1]; p.k[1] = (const char*)d_in[6];
    p.tau = (uint32_t)(TAU * tscale + 0.5); p.tauo = (uint32_t)(TAUO * tscale + 0.5); p.gap = (uint32_t)(GAP * tscale + 0.5);
    p.first = (uint32_t)((NINIT * TAU - OFFS) * tscale + 0.5);
    p.out = (__nv_bfloat16*)d_out;
    p.ox = (uint32_t*)ox; p.epoch = (uint32_t*)epoch;
    cudaLaunchConfig_t cfg = {};
    cfg.gridDim = dim3(NCTA);
    cfg.blockDim = dim3(NTHR);
    cfg.dynamicSmemBytes = SM_TOTAL;
    cfg.stream = cudaStreamPerThread;
    cudaLaunchAttribute attr;
    attr.id = cudaLaunchAttributeCooperative;
    attr.val.cooperative = 1;
    cfg.attrs = &attr;
    cfg.numAttrs = 1;
    cudaLaunchKernelEx(&cfg, fused_decode_kernel, p, m);
}
```
